```python
import torch

def _softmax(x, axis=-1):
    return torch.softmax(x, dim=axis)
def _gelu(x):
    return torch.nn.functional.gelu(x, approximate="tanh")
def _silu(x):
    return torch.nn.functional.silu(x)
def _sigmoid(x):
    return torch.sigmoid(x)
def _layernorm(x, axis=-1, eps=1e-5):
    m = x.mean(dim=axis, keepdim=True)
    v = x.var(dim=axis, keepdim=True, unbiased=False)
    return (x - m) / torch.sqrt(v + eps)
def _scatter_add(tgt, idx, src, axis=0):
    return tgt.clone().index_add_(axis, idx, src)
def _segment_sum(src, seg, n):
    out = torch.zeros((n,) + src.shape[1:], dtype=src.dtype)
    return out.index_add_(0, seg, src)
def _pad(x, pw):
    flat = tuple(v for pair in reversed(pw) for v in pair)
    return torch.nn.functional.pad(x, flat)

kernel_name = 'standalone__depthwise_separable__vision'

def setup_inputs():

    _w = (lambda a: (lambda t: t.to(torch.bfloat16) if t.is_floating_point() else t)(torch.as_tensor(a)))
    H = W = 384
    C = 384
    k = 1
    return {
        "x": _w((lambda *s: torch.randn(*s, dtype=torch.bfloat16) * 0.05)(1, H, W, C)),
        "dw": _w((lambda *s: torch.randn(*s, dtype=torch.bfloat16) * 0.05)(k, k, C)),
        "pw": _w((lambda *s: torch.randn(*s, dtype=torch.bfloat16) * 0.05)(C, C)),
    }

def reference(x, dw, pw):
    B, H, W, C = x.shape
    k = dw.shape[0]
    pad = k // 2
    xp = _pad(x, ((0,0),(pad,pad),(pad,pad),(0,0)))
    out = torch.zeros_like(x)
    for i in range(k):
        for j in range(k):
            out = out + xp[:, i:i+H, j:j+W, :] * dw[i, j][None, None, None, :]
    return torch.einsum('bhwc,cd->bhwd', out, pw)
```

```cpp
#include <cuda_runtime.h>
#include <cuda_bf16.h>
#include <cuda.h>
#include <stdint.h>

namespace {

constexpr int kC = 384;
constexpr int kTilePx = 32;
constexpr int kStages = 5;
constexpr int kOutBufs = 8;
constexpr int kPark = 5;
constexpr int kThreads = 512;
constexpr int kStageBytes = kTilePx * kC * 2;
constexpr int kOutBytes = kTilePx * 192 * 2;
constexpr int kWChunkBytes = 64 * 192 * 2;
constexpr int kXSlabBytes = 64 * 128 * 2;
constexpr int kWOff = 2 * kStageBytes;
constexpr int kOutOff = kStages * kStageBytes;
constexpr int kDwOff = kOutOff + kOutBufs * kOutBytes;
constexpr int kFullOff = kDwOff + kC * 2;
constexpr int kEmptyOff = kFullOff + 8 * kStages;
constexpr int kOFullOff = kEmptyOff + 8 * kStages;
constexpr int kOEmptyOff = kOFullOff + 8 * kOutBufs;
constexpr int kWBarOff = kOEmptyOff + 8 * kOutBufs;
constexpr int kXBarOff = kWBarOff + 8 * 3;
constexpr int kDwBarOff = kXBarOff + 8 * 3;
constexpr int kSlotOff = kDwBarOff + 8;
constexpr int kOSlotOff = kSlotOff + 4 * kStages;
constexpr int kPSlotOff = kOSlotOff + 4 * kOutBufs;
constexpr int kPlanOff = kPSlotOff + 4 * kPark;
constexpr int kPullBarOff = (kPlanOff + 8 + 7) / 8 * 8;
constexpr int kPullOff = (kPullBarOff + 8 + 127) / 128 * 128;
constexpr int kPullBytes = kStageBytes / 8;
constexpr int kSmemBytes = kPullOff + kPullBytes + 1024;
static_assert(kWChunkBytes == kStageBytes && kWOff + 6 * kWChunkBytes <= kDwOff, "weight staging");
static_assert(kSmemBytes <= 232448, "shared memory");

struct Knobs {
    int first_gap;
    int pf_t0, pf_dt;
    int static_tiles;
    int park_from;
    int pull_to;
    int end_dt, end_step, end_tiles;
    int hold_pos[6], hold[6];
    int lead_pos[10], lead[10];
};
#define DEFAULT_KNOBS {430, 26, 813, 22, 3414, 486, 5410, 415, 7, \
    {0, 412, 555, 728, 1105, 4281}, {0, 2, 1, 2, 3, 1}, \
    {872, 890, 1566, 2081, 2529, 2972, 3418, 3710, 4300, 4319}, {289, 500, 535, 333, 321, 195, -5, 210, 180, 151}}
#define KNOB_PARAM
#define KNOB_ARG
#define KNOB_DECL constexpr Knobs kn = DEFAULT_KNOBS;

__device__ unsigned long long g_out_of_tiles;
__device__ unsigned int g_tile_counter;

__device__ __forceinline__ uint32_t smem_u32(const void* p) { return (uint32_t)__cvta_generic_to_shared(p); }

__device__ __forceinline__ void mbar_init(uint32_t bar, uint32_t cnt) {
    asm volatile("mbarrier.init.shared::cta.b64 [%0], %1;" ::"r"(bar), "r"(cnt) : "memory");
}
__device__ __forceinline__ void mbar_expect_tx(uint32_t bar, uint32_t bytes) {
    asm volatile("mbarrier.arrive.expect_tx.shared::cta.b64 _, [%0], %1;" ::"r"(bar), "r"(bytes) : "memory");
}
__device__ __forceinline__ void mbar_arrive(uint32_t bar) {
    asm volatile("mbarrier.arrive.shared::cta.b64 _, [%0];" ::"r"(bar) : "memory");
}
__device__ __forceinline__ void mbar_arrive_cluster(uint32_t bar) {
    asm volatile("mbarrier.arrive.shared::cluster.b64 _, [%0];" ::"r"(bar) : "memory");
}
__device__ __forceinline__ void mbar_wait(uint32_t bar, uint32_t parity) {
    asm volatile(
        "{\n.reg .pred p;\n.reg .u32 n;\n"
        "mbarrier.try_wait.parity.shared::cta.b64 p, [%0], %1;\n"
        "@p bra DONE;\n"
        "mov.u32 n, 0;\n"
        "LOOP:\n"
        "mbarrier.try_wait.parity.shared::cta.b64 p, [%0], %1;\n"
        "@p bra DONE;\n"
        "add.u32 n, n, 1;\n"
        "setp.lt.u32 p, n, 4194304;\n"
        "@p bra LOOP;\n"
        "trap;\n"
        "DONE:\n}" ::"r"(bar), "r"(parity) : "memory");
}
__device__ __forceinline__ bool mbar_try(uint32_t bar, uint32_t parity) {
    uint32_t ok;
    asm volatile("{\n.reg .pred p;\nmbarrier.try_wait.parity.shared::cta.b64 p, [%1], %2;\nselp.u32 %0, 1, 0, p;\n}"
                 : "=r"(ok) : "r"(bar), "r"(parity) : "memory");
    return ok;
}
__device__ __forceinline__ uint32_t map_to_cta(uint32_t addr, uint32_t cta) {
    uint32_t r;
    asm("mapa.shared::cluster.u32 %0, %1, %2;" : "=r"(r) : "r"(addr), "r"(cta));
    return r;
}
__device__ __forceinline__ void named_bar_sync(int id, int n) { asm volatile("bar.sync %0, %1;" ::"r"(id), "r"(n) : "memory"); }
__device__ __forceinline__ void named_bar_arrive(int id, int n) { asm volatile("bar.arrive %0, %1;" ::"r"(id), "r"(n) : "memory"); }
__device__ __forceinline__ void cluster_arrive() {
    __syncwarp();
    asm volatile("barrier.cluster.arrive.relaxed.aligned;" ::: "memory");
}
__device__ __forceinline__ void cluster_wait() {
    __syncwarp();
    asm volatile("barrier.cluster.wait.acquire.aligned;" ::: "memory");
}
__device__ __forceinline__ void prefetch_line(const void* p) { asm volatile("prefetch.global.L2 [%0];" ::"l"(p) : "memory"); }
__device__ __forceinline__ void prefetch_map(const CUtensorMap* m) { asm volatile("prefetch.tensormap [%0];" ::"l"(m) : "memory"); }
__device__ __forceinline__ uint32_t globaltimer() {
    uint32_t t;
    asm volatile("mov.u32 %0, %%globaltimer_lo;" : "=r"(t));
    return t;
}
__device__ __forceinline__ uint32_t clock32() {
    uint32_t t;
    asm volatile("mov.u32 %0, %%clock;" : "=r"(t));
    return t;
}
__device__ __forceinline__ int lds32(uint32_t addr) {
    int v;
    asm volatile("ld.shared.b32 %0, [%1];" : "=r"(v) : "r"(addr) : "memory");
    return v;
}
__device__ __forceinline__ int lds32_volatile(uint32_t addr) {
    int v;
    asm volatile("ld.volatile.shared.b32 %0, [%1];" : "=r"(v) : "r"(addr) : "memory");
    return v;
}
__device__ __forceinline__ uint32_t wait_nonzero(uint32_t addr) {
    uint32_t v;
    asm volatile(
        "{\n.reg .pred p;\n.reg .u32 n;\nmov.u32 n, 0;\n"
        "LOOP:\n"
        "ld.volatile.shared.b32 %0, [%1];\n"
        "setp.ne.u32 p, %0, 0;\n"
        "@p bra DONE;\n"
        "nanosleep.u32 20;\n"
        "add.u32 n, n, 1;\n"
        "setp.lt.u32 p, n, 4194304;\n"
        "@p bra LOOP;\n"
        "trap;\n"
        "DONE:\n}" : "=r"(v) : "r"(addr) : "memory");
    return v;
}
__device__ __forceinline__ void sts32(uint32_t addr, int v) { asm volatile("st.shared.b32 [%0], %1;" ::"r"(addr), "r"(v) : "memory"); }

#define ACC4(o) "+f"(d[o]), "+f"(d[o + 1]), "+f"(d[o + 2]), "+f"(d[o + 3])
#define ACC16(o) ACC4(o), ACC4(o + 4), ACC4(o + 8), ACC4(o + 12)
__device__ __forceinline__ void wgmma_rs(float (&d)[32], const uint32_t (&a)[4], uint64_t desc_b, int scale_d) {
    asm volatile(
        "{\n.reg .pred p;\nsetp.ne.b32 p, %37, 0;\n"
        "wgmma.mma_async.sync.aligned.m64n64k16.f32.bf16.bf16 "
        "{%0, %1, %2, %3, %4, %5, %6, %7, %8, %9, %10, %11, %12, %13, %14, %15, "
        "%16, %17, %18, %19, %20, %21, %22, %23, %24, %25, %26, %27, %28, %29, %30, %31}, "
        "{%32, %33, %34, %35}, %36, p, 1, 1, 0;\n}"
        : ACC16(0), ACC16(16)
        : "r"(a[0]), "r"(a[1]), "r"(a[2]), "r"(a[3]), "l"(desc_b), "r"(scale_d));
}
__device__ __forceinline__ void wgmma_rs(float (&d)[16], const uint32_t (&a)[4], uint64_t desc_b, int scale_d) {
    asm volatile(
        "{\n.reg .pred p;\nsetp.ne.b32 p, %21, 0;\n"
        "wgmma.mma_async.sync.aligned.m64n32k16.f32.bf16.bf16 "
        "{%0, %1, %2, %3, %4, %5, %6, %7, %8, %9, %10, %11, %12, %13, %14, %15}, "
        "{%16, %17, %18, %19}, %20, p, 1, 1, 0;\n}"
        : ACC16(0)
        : "r"(a[0]), "r"(a[1]), "r"(a[2]), "r"(a[3]), "l"(desc_b), "r"(scale_d));
}
__device__ __forceinline__ uint64_t make_desc(uint32_t addr, uint32_t group_stride) {
    return (uint64_t(1) << 62) | (uint64_t(group_stride >> 4) << 32) | (uint64_t(1) << 16) | (uint64_t)((addr & 0x3FFFF) >> 4);
}
__device__ __forceinline__ constexpr uint64_t desc_k(int k) { return (uint64_t)(((k >> 2) * 1024 + (k & 3) * 32) >> 4); }

__device__ __forceinline__ uint32_t pack_bf16(float lo, float hi) {
    uint32_t r;
    asm("cvt.rn.bf16x2.f32 %0, %1, %2;" : "=r"(r) : "f"(hi), "f"(lo));
    return r;
}
__device__ __forceinline__ uint32_t mul_bf16x2(uint32_t a, uint32_t b) {
    uint32_t r;
    asm("mul.rn.bf16x2 %0, %1, %2;" : "=r"(r) : "r"(a), "r"(b));
    return r;
}

__global__ void __cluster_dims__(2, 1, 1) __launch_bounds__(kThreads, 1)
dwsep_kernel(const __grid_constant__ CUtensorMap tm_w, const __grid_constant__ CUtensorMap tm_x0,
             const __grid_constant__ CUtensorMap tm_x, const __grid_constant__ CUtensorMap tm_o,
             const __grid_constant__ CUtensorMap tm_s,
             const __nv_bfloat16* __restrict__ x, const __nv_bfloat16* __restrict__ dw,
             const __nv_bfloat16* __restrict__ pw, int num_tiles KNOB_PARAM) {
    KNOB_DECL
    extern __shared__ uint8_t smem_raw[];
    const uint32_t sb = (smem_u32(smem_raw) + 1023u) & ~1023u;

    uint32_t rank;
    asm("mov.u32 %0, %%cluster_ctarank;" : "=r"(rank));
    const int cluster = blockIdx.x >> 1;
    auto static_tile = [&](int i) { return (i >> 1) * gridDim.x + cluster * 2 + (i & 1); };

    if (threadIdx.x < 32) {
        prefetch_line(threadIdx.x < 18 ? (const char*)pw + (blockIdx.x & 127) * 2304 + threadIdx.x * 128
                                       : (const char*)dw + min(threadIdx.x - 18, 5) * 128);
    } else if (threadIdx.x < 224) {
        const uint32_t c0 = __shfl_sync(0xffffffffu, clock32(), 0), chunk = (threadIdx.x >> 5) - 1;
        const uint32_t delay = ((chunk >> 1) * gridDim.x + blockIdx.x) * kn.first_gap >> 7;
        for (int n = 0; clock32() - c0 < delay && n < 1024; n++) {}
        prefetch_line((const char*)x + (size_t)blockIdx.x * kStageBytes + (threadIdx.x & 31) * 768 + chunk * 128);
    } else if (threadIdx.x == 288) {
        prefetch_map(&tm_w);
        prefetch_map(&tm_x0);
    }
    if (threadIdx.x >> 5 == 8) {
        if (threadIdx.x == 256) {
#pragma unroll
            for (int b = 0; b < 7; b++) mbar_init(sb + kWBarOff + 8 * b, 1);
            asm volatile("fence.proxy.async.shared::cta;" ::: "memory");
        }
        __syncwarp();
        named_bar_arrive(8, 384);
        if (threadIdx.x == 256) {
            mbar_expect_tx(sb + kDwBarOff, kC * 2);
            asm volatile("cp.async.bulk.shared::cluster.global.mbarrier::complete_tx::bytes [%0], [%1], %2, [%3];"
                         ::"r"(sb + kDwOff), "l"(dw), "r"(kC * 2), "r"(sb + kDwBarOff) : "memory");
#pragma unroll
            for (int j = 0; j < 3; j++) {
                mbar_expect_tx(sb + kWBarOff + 8 * j, 2 * kWChunkBytes);
#pragma unroll
                for (int c = 2 * j; c < 2 * j + 2; c++)
                    asm volatile("cp.async.bulk.tensor.3d.shared::cluster.global.mbarrier::complete_tx::bytes [%0], [%1, {%3, %4, %5}], [%2];"
                                 ::"r"(sb + kWOff + c * kWChunkBytes), "l"(&tm_w), "r"(sb + kWBarOff + 8 * j), "r"(0), "r"(c * 64),
                                   "r"((int)rank * 3) : "memory");
                mbar_expect_tx(sb + kXBarOff + 8 * j, kXSlabBytes);
                asm volatile("cp.async.bulk.tensor.4d.shared::cluster.global.mbarrier::complete_tx::bytes [%0], [%1, {%3, %3, %4, %5}], [%2];"
                             ::"r"(sb + j * kXSlabBytes), "l"(&tm_x0), "r"(sb + kXBarOff + 8 * j), "r"(0), "r"(2 * j),
                               "r"(cluster * 8) : "memory");
            }
        }
        __syncwarp();
    }

    if (threadIdx.x < 384) {
        asm volatile("setmaxnreg.inc.sync.aligned.u32 160;");
        cluster_arrive();
        if (threadIdx.x >> 5 != 8) named_bar_sync(8, 384);
        const int wg = __shfl_sync(0xffffffffu, threadIdx.x >> 7, 0);
        const int warp = (threadIdx.x >> 5) & 3;
        const int lane = threadIdx.x & 31;
        const int mi = lane >> 3, ri = lane & 7;
        const uint32_t leader_empty = map_to_cta(sb + kEmptyOff, 0);
        const uint32_t st_off = sb + kOutOff + (((mi >> 1) * 8 + ri) * 3 + wg) * 128 + (((2 * warp + (mi & 1)) ^ ((3 * ri + wg) & 7)) << 4);
        int s = 0, ob = 0;
        uint32_t ph = 0, oph = 1;
        auto release_stage = [&]() {
            if (lane == 0) mbar_arrive_cluster(leader_empty + 8 * s);
            if (++s == kStages) { s = 0; ph ^= 1; }
        };
        auto pack = [&](uint32_t (&p)[8], const float* acc) {
#pragma unroll
            for (int k = 0; k < 8; k++) p[k] = pack_bf16(acc[2 * k], acc[2 * k + 1]);
        };
        auto put = [&](const uint32_t (&p)[8], int t) {
            mbar_wait(sb + kOEmptyOff + 8 * ob, oph);
            if (threadIdx.x == 0) sts32(sb + kOSlotOff + 4 * ob, t);
#pragma unroll
            for (int q = 0; q < 2; q++)
                asm volatile("stmatrix.sync.aligned.m8n8.x4.trans.shared.b16 [%0], {%1, %2, %3, %4};"
                             ::"r"(st_off + ob * kOutBytes + q * (16 * 384)), "r"(p[4 * q]), "r"(p[4 * q + 1]),
                               "r"(p[4 * q + 2]), "r"(p[4 * q + 3]) : "memory");
            asm volatile("fence.proxy.async.shared::cta;" ::: "memory");
            __syncwarp();
            if (lane == 0) mbar_arrive(sb + kOFullOff + 8 * ob);
            if (++ob == kOutBufs) { ob = 0; oph ^= 1; }
        };
        auto my_turn = [&]() { named_bar_sync(2 + wg, 256); };
        auto pass_turn = [&]() { named_bar_arrive(wg == 2 ? 2 : 3 + wg, 256); };
        if (wg == 2) pass_turn();

        uint32_t a[24][4];
        {
            float acc0[32];
            uint32_t dws[48];
            mbar_wait(sb + kDwBarOff, 0);
#pragma unroll
            for (int k = 0; k < 48; k++) dws[k] = lds32(sb + kDwOff + k * 16 + (lane & 3) * 4);
            cluster_wait();
            const uint32_t wbase = sb + kWOff + wg * 8192 + ((mi >> 1) * 8 + ri) * 128 + (((2 * warp + (mi & 1)) ^ ri) << 4);
            const uint64_t desc = make_desc(sb, 2048);
#pragma unroll
            for (int j = 0; j < 3; j++) {
                mbar_wait(sb + kWBarOff + 8 * j, 0);
#pragma unroll
                for (int k = 8 * j; k < 8 * j + 8; k++) {
                    asm volatile("ldmatrix.sync.aligned.m8n8.x4.trans.shared.b16 {%0, %1, %2, %3}, [%4];"
                                 : "=r"(a[k][0]), "=r"(a[k][1]), "=r"(a[k][2]), "=r"(a[k][3])
                                 : "r"(wbase + (k >> 2) * kWChunkBytes + (k & 3) * 2048) : "memory");
                    a[k][0] = mul_bf16x2(a[k][0], dws[2 * k]);
                    a[k][1] = mul_bf16x2(a[k][1], dws[2 * k]);
                    a[k][2] = mul_bf16x2(a[k][2], dws[2 * k + 1]);
                    a[k][3] = mul_bf16x2(a[k][3], dws[2 * k + 1]);
                }
                if (lane >> 1 == j + 1 && lane < kStages) mbar_arrive_cluster(leader_empty + 8 * lane);
                if (j == 2) {
                    named_bar_arrive(wg == 0 ? 6 : 5, 384);
                    named_bar_arrive(wg == 2 ? 6 : 7, 384);
                }
                mbar_wait(sb + kXBarOff + 8 * j, 0);
                my_turn();
                asm volatile("wgmma.fence.sync.aligned;" ::: "memory");
#pragma unroll
                for (int k = 0; k < 8; k++) wgmma_rs(acc0, a[8 * j + k], desc + (j * kXSlabBytes >> 4) + desc_k(k), j + k != 0);
                pass_turn();
            }
            asm volatile("wgmma.commit_group.sync.aligned;" ::: "memory");
            named_bar_sync(5 + wg, 384);
            asm volatile("wgmma.wait_group.sync.aligned 0;" ::: "memory");
            release_stage();
            release_stage();
            uint32_t p[8];
            pack(p, acc0);
            put(p, static_tile(0));
            pack(p, acc0 + 16);
            put(p, static_tile(1));
        }

        float acc[16];
        uint32_t park[kPark][8];
        int parked = 0;
#pragma unroll
        for (int k = 0; k < kPark * 8; k++) asm volatile("mov.b32 %0, 0;" : "=r"(park[k / 8][k % 8]));
#pragma unroll 1
        while (true) {
            mbar_wait(sb + kFullOff + 8 * s, ph);
            const int t = lds32(sb + kSlotOff + 4 * s);
            if (t >= num_tiles) break;
            const uint64_t desc = make_desc(sb + s * kStageBytes, 6144);
            my_turn();
            asm volatile("wgmma.fence.sync.aligned;" ::: "memory");
#pragma unroll
            for (int k = 0; k < 24; k++) {
                if (k == 20) pass_turn();
                wgmma_rs(acc, a[k], desc + desc_k(k), k != 0);
            }
            asm volatile("wgmma.commit_group.sync.aligned;" ::: "memory");
            asm volatile("wgmma.wait_group.sync.aligned 0;" ::: "memory");
            release_stage();
            if (t >= kn.park_from && parked < kPark) {
#pragma unroll
                for (int k = 0; k < kPark; k++)
                    if (parked == k) pack(park[k], acc);
                if (threadIdx.x == 0) sts32(sb + kPSlotOff + 4 * parked, t);
                parked++;
            } else {
                uint32_t p[8];
                pack(p, acc);
                put(p, t);
            }
        }
#pragma unroll
        for (int k = 0; k < kPark; k++)
            if (k < parked) put(park[k], threadIdx.x == 0 ? lds32(sb + kPSlotOff + 4 * k) : 0);
    } else {
        asm volatile("setmaxnreg.dec.sync.aligned.u32 32;");
        const int role = (threadIdx.x >> 5) & 3;
        const bool lead = (threadIdx.x & 31) == 0;
        if (role >= 2) {
            const int par = role & 1;
            if (lead) {
                if (par == 0) {
#pragma unroll
                    for (int b = 0; b < kOutBufs; b++) {
                        mbar_init(sb + kOFullOff + 8 * b, 12);
                        mbar_init(sb + kOEmptyOff + 8 * b, 1);
                    }
                } else {
#pragma unroll
                    for (int s = 0; s < kStages; s++) {
                        mbar_init(sb + kFullOff + 8 * s, 1);
                        mbar_init(sb + kEmptyOff + 8 * s, 24);
                        if (s < 2) {
                            mbar_arrive(sb + kFullOff + 8 * s);
                            asm volatile("mbarrier.arrive.shared::cta.b64 _, [%0], 24;" ::"r"(sb + kEmptyOff + 8 * s) : "memory");
                        }
                    }
                    prefetch_map(&tm_x);
                    prefetch_map(&tm_o);
                    prefetch_map(&tm_s);
                }
                asm volatile("fence.mbarrier_init.release.cluster;" ::: "memory");
            }
            cluster_arrive();
            cluster_wait();
            if (lead) {
                uint64_t streaming;
                asm volatile("createpolicy.fractional.L2::evict_first.b64 %0, 1.0;" : "=l"(streaming));
                int head = par, tail = par, held = 0, pos = 0;
                int index = par, last;
                uint32_t ph = 0;
                auto advance = [&]() { if ((head += 2) >= kOutBufs) { head = par; ph ^= 1; } };
                auto issue = [&](bool hint) {
                    const int px = lds32(sb + kOSlotOff + 4 * tail) * kTilePx;
                    if (hint)
                        asm volatile("cp.async.bulk.tensor.3d.global.shared::cta.bulk_group.L2::cache_hint [%0, {%2, %3, %4}], [%1], %5;"
                                     ::"l"(&tm_o), "r"(sb + kOutOff + tail * kOutBytes), "r"(0), "r"((int)rank * 3), "r"(px), "l"(streaming) : "memory");
                    else
                        asm volatile("cp.async.bulk.tensor.3d.global.shared::cta.bulk_group [%0, {%2, %3, %4}], [%1];"
                                     ::"l"(&tm_o), "r"(sb + kOutOff + tail * kOutBytes), "r"(0), "r"((int)rank * 3), "r"(px) : "memory");
                    asm volatile("cp.async.bulk.commit_group;" ::: "memory");
                    if ((tail += 2) >= kOutBufs) tail = par;
                    index += 2;
                };
#pragma unroll 1
                while (true) {
                    bool got = false;
#pragma unroll 1
                    for (int q = 0; q < 1 << 22 && !got; q++) {
                        last = lds32_volatile(sb + kPlanOff);
                        if (last - index < kOutBufs) break;
                        got = mbar_try(sb + kOFullOff + 8 * head, ph);
                    }
                    if (!got) break;
                    pos = max(pos, lds32(sb + kOSlotOff + 4 * head));
                    held++;
                    advance();
                    int hold = 0;
#pragma unroll
                    for (int k = 0; k < 6; k++)
                        if (pos >= kn.hold_pos[k]) hold = kn.hold[k];
                    int freed = tail, n = 0;
#pragma unroll 1
                    for (; held > hold; held--, n++) issue(pos >= kn.hold_pos[5]);
#pragma unroll 1
                    while (n-- > 0) {
                        if (n == 0) asm volatile("cp.async.bulk.wait_group.read 0;" ::: "memory");
                        else if (n == 1) asm volatile("cp.async.bulk.wait_group.read 1;" ::: "memory");
                        else if (n == 2) asm volatile("cp.async.bulk.wait_group.read 2;" ::: "memory");
                        else asm volatile("cp.async.bulk.wait_group.read 3;" ::: "memory");
                        mbar_arrive(sb + kOEmptyOff + 8 * freed);
                        if ((freed += 2) >= kOutBufs) freed = par;
                    }
                }
#pragma unroll 1
                while (index <= last) {
                    if (held == 0) {
                        mbar_wait(sb + kOFullOff + 8 * head, ph);
                        advance();
                    } else {
                        held--;
                    }
                    const int left = last - index;
                    if (left < kn.end_tiles) {
                        const uint32_t due = wait_nonzero(sb + kPlanOff + 4) - left * kn.end_step;
                        for (int q = 0; (int)(globaltimer() - due) < 0 && q < 4096; q++) __nanosleep(20);
                    }
                    issue(false);
                }
                wait_nonzero(sb + kPlanOff + 4);
                asm volatile("cp.async.bulk.wait_group.read 0;" ::: "memory");
            }
        } else if (role == 1) {
            const uint32_t t_start = __shfl_sync(0xffffffffu, globaltimer(), 0);
            const uint32_t my_slot = sb + kSlotOff + 4 * min(threadIdx.x & 31, kStages - 1);
            sts32(my_slot, 0);
            sts32(sb + kPlanOff, 1 << 20);
            sts32(sb + kPlanOff + 4, 0);
            __threadfence_block();
            cluster_arrive();
#pragma unroll 1
            for (int t = blockIdx.x + gridDim.x; t < num_tiles; t += gridDim.x) {
                const uint32_t due = kn.pf_t0 + (t - gridDim.x) * kn.pf_dt / gridDim.x;
                for (int n = 0; globaltimer() - t_start < due && n < 4096; n++) __nanosleep(50);
                int p0 = 0, p1 = 1, l0 = kn.lead[0], l1 = kn.lead[0];
#pragma unroll
                for (int k = 0; k < 9; k++)
                    if (t >= kn.lead_pos[k]) { p0 = kn.lead_pos[k]; p1 = kn.lead_pos[k + 1]; l0 = kn.lead[k]; l1 = kn.lead[k + 1]; }
                const int max_lead = l0 + (min(t, p1) - p0) * (l1 - l0) / (p1 - p0);
                for (int n = 0; t > max_lead && n < 4096; n++) {
                    const int front = __reduce_max_sync(0xffffffffu, lds32_volatile(my_slot));
                    if (t - max_lead <= front || front >= num_tiles) break;
                    __nanosleep(50);
                }
                if (lead) {
                    if (t >= 2 * gridDim.x && t < kn.pull_to) {
                        asm volatile("mbarrier.expect_tx.relaxed.cta.shared::cta.b64 [%0], %1;" ::"r"(sb + kPullBarOff), "r"(kPullBytes) : "memory");
                        asm volatile("cp.async.bulk.tensor.2d.shared::cluster.global.mbarrier::complete_tx::bytes [%0], [%1, {%3, %4}], [%2];"
                                     ::"r"(sb + kPullOff), "l"(&tm_s), "r"(sb + kPullBarOff), "r"(0), "r"(t * (kStageBytes / 128)) : "memory");
                    } else {
                        asm volatile("cp.async.bulk.prefetch.L2.global [%0], %1;"
                                     ::"l"((const char*)x + (size_t)t * kStageBytes), "r"(kStageBytes) : "memory");
                        if (t < 2 * gridDim.x) {
                            mbar_init(sb + kPullBarOff, 1);
                            asm volatile("fence.proxy.async.shared::cta;" ::: "memory");
                        }
                    }
                }
            }
            if (lead) {
                mbar_arrive(sb + kPullBarOff);
                mbar_wait(sb + kPullBarOff, 0);
            }
            cluster_wait();
        } else {
            cluster_arrive();
            cluster_wait();
            if (lead && rank == 0) {
                const uint32_t peer = map_to_cta(sb, 1);
                const int nstatic = kn.static_tiles * (gridDim.x >> 1);
                const unsigned last_fetch = num_tiles - nstatic + gridDim.x - 1;
                int s = 2, i = 2;
                uint32_t ph = 0;
                auto step = [&](unsigned& raw) -> bool {
                    const int t = nstatic + raw;
                    const bool valid = t < num_tiles;
                    raw = static_tile(i + 2) - nstatic;
                    if (i + 2 >= kn.static_tiles && valid)
                        asm volatile("atom.global.inc.u32 %0, [%1], %2;" : "+r"(raw) : "l"(&g_tile_counter), "r"(last_fetch) : "memory");
                    mbar_wait(sb + kEmptyOff + 8 * s, ph);
                    const uint32_t full = kFullOff + 8 * s, slot = kSlotOff + 4 * s;
                    const uint32_t bytes = valid ? kStageBytes : 0;
                    sts32(sb + slot, t);
                    mbar_expect_tx(sb + full, bytes);
                    asm volatile("mbarrier.arrive.expect_tx.shared::cluster.b64 _, [%0], %1;" ::"r"(peer + full), "r"(bytes + 4) : "memory");
                    asm volatile("st.async.weak.shared::cluster.mbarrier::complete_tx::bytes.b32 [%0], %1, [%2];"
                                 ::"r"(peer + slot), "r"(t), "r"(peer + full) : "memory");
                    if (!valid) return false;
                    asm volatile(
                        "cp.async.bulk.tensor.4d.shared::cluster.global.mbarrier::complete_tx::bytes.multicast::cluster "
                        "[%0], [%1, {%3, %3, %3, %4}], [%2], %5;"
                        ::"r"(sb + s * kStageBytes), "l"(&tm_x), "r"(sb + full), "r"(0), "r"(t * (kTilePx / 8)),
                          "h"((uint16_t)3) : "memory");
                    if (++s == kStages) { s = 0; ph ^= 1; }
                    i++;
                    return true;
                };
                unsigned raw0 = static_tile(2) - nstatic, raw1 = static_tile(3) - nstatic;
#pragma unroll 1
                while (step(raw0) && step(raw1)) {}
                unsigned long long now;
                asm volatile("mov.u64 %0, %%globaltimer;" : "=l"(now));
                asm volatile("red.relaxed.gpu.global.max.u64 [%0], %1;" ::"l"(&g_out_of_tiles), "l"(now) : "memory");
                sts32(sb + kPlanOff, i - 1);
                asm volatile("st.shared::cluster.b32 [%0], %1;" ::"r"(peer + kPlanOff), "r"(i - 1) : "memory");
#pragma unroll 1
                for (int k = 1; k < kStages; k++) {
                    if (++s == kStages) { s = 0; ph ^= 1; }
                    mbar_wait(sb + kEmptyOff + 8 * s, ph);
                    if (k == 2) {
                        asm volatile("ld.relaxed.gpu.global.u64 %0, [%1];" : "=l"(now) : "l"(&g_out_of_tiles) : "memory");
                        const uint32_t end = ((uint32_t)now + kn.end_dt) | 1;
                        sts32(sb + kPlanOff + 4, end);
                        asm volatile("st.shared::cluster.b32 [%0], %1;" ::"r"(peer + kPlanOff + 4), "r"(end) : "memory");
                    }
                }
            }
        }
    }
}

typedef CUresult (*EncodeTiledFn)(CUtensorMap*, CUtensorMapDataType, cuuint32_t, void*, const cuuint64_t*,
                                  const cuuint64_t*, const cuuint32_t*, const cuuint32_t*, CUtensorMapInterleave,
                                  CUtensorMapSwizzle, CUtensorMapL2promotion, CUtensorMapFloatOOBfill);

}

extern "C" void kernel_launch(void* const* d_in, const int* in_sizes, int n_in, void* d_out, int out_size) {
    (void)n_in; (void)out_size;
    const __nv_bfloat16* x = (const __nv_bfloat16*)d_in[0];
    const __nv_bfloat16* dw = (const __nv_bfloat16*)d_in[1];
    const __nv_bfloat16* pw = (const __nv_bfloat16*)d_in[2];
    const int pixels = in_sizes[0] / kC;

    static EncodeTiledFn encode = nullptr;
    static int grid = 0;
    if (!encode) {
        void* fn = nullptr;
        cudaDriverEntryPointQueryResult qr;
        cudaGetDriverEntryPoint("cuTensorMapEncodeTiled", &fn, cudaEnableDefault, &qr);
        encode = (EncodeTiledFn)fn;
        cudaFuncSetAttribute(dwsep_kernel, cudaFuncAttributeMaxDynamicSharedMemorySize, kSmemBytes);
        int sms = 0, clusters = 0;
        cudaDeviceGetAttribute(&sms, cudaDevAttrMultiProcessorCount, 0);
        cudaLaunchConfig_t cfg = {};
        cudaLaunchAttribute attr = {};
        attr.id = cudaLaunchAttributeClusterDimension;
        attr.val.clusterDim.x = 2;
        attr.val.clusterDim.y = attr.val.clusterDim.z = 1;
        cfg.gridDim = dim3(sms & ~1);
        cfg.blockDim = dim3(kThreads);
        cfg.dynamicSmemBytes = kSmemBytes;
        cfg.attrs = &attr;
        cfg.numAttrs = 1;
        if (cudaOccupancyMaxActiveClusters(&clusters, dwsep_kernel, &cfg) != cudaSuccess || clusters < 1) {
            (void)cudaGetLastError();
            clusters = sms / 2;
        }
        grid = 2 * (clusters < sms / 2 ? clusters : sms / 2);
    }

    CUtensorMap tm_w, tm_x0, tm_x, tm_o, tm_s;
    auto make_map = [&](CUtensorMap* m, const void* base, int rank, const cuuint64_t* dims, const cuuint64_t* strides,
                        const cuuint32_t* box, CUtensorMapL2promotion promo,
                        CUtensorMapSwizzle swizzle = CU_TENSOR_MAP_SWIZZLE_128B) {
        const cuuint32_t ones[4] = {1, 1, 1, 1};
        encode(m, CU_TENSOR_MAP_DATA_TYPE_BFLOAT16, rank, (void*)base, dims, strides, box, ones,
               CU_TENSOR_MAP_INTERLEAVE_NONE, swizzle, promo, CU_TENSOR_MAP_FLOAT_OOB_FILL_NONE);
    };
    {
        const cuuint64_t dims[3] = {64, kC, 6}, strides[2] = {kC * 2, 128};
        const cuuint32_t box[3] = {64, 64, 3};
        make_map(&tm_w, pw, 3, dims, strides, box, CU_TENSOR_MAP_L2_PROMOTION_L2_128B);
    }
    {
        const cuuint64_t dims[4] = {64, 8, 6, (cuuint64_t)pixels / 8}, strides[3] = {kC * 2, 128, kC * 2 * 8};
        const cuuint32_t box0[4] = {64, 8, 2, 8}, box[4] = {64, 8, 6, kTilePx / 8};
        make_map(&tm_x0, x, 4, dims, strides, box0, CU_TENSOR_MAP_L2_PROMOTION_L2_128B);
        make_map(&tm_x, x, 4, dims, strides, box, CU_TENSOR_MAP_L2_PROMOTION_L2_128B);
    }
    {
        const cuuint64_t dims[2] = {8, (cuuint64_t)pixels * 6}, strides[1] = {128};
        const cuuint32_t box[2] = {8, kStageBytes / 128};
        make_map(&tm_s, x, 2, dims, strides, box, CU_TENSOR_MAP_L2_PROMOTION_L2_128B, CU_TENSOR_MAP_SWIZZLE_NONE);
    }
    {
        const cuuint64_t dims[3] = {64, 6, (cuuint64_t)pixels}, strides[2] = {128, kC * 2};
        const cuuint32_t box[3] = {64, 3, kTilePx};
        make_map(&tm_o, d_out, 3, dims, strides, box, CU_TENSOR_MAP_L2_PROMOTION_NONE);
    }
    dwsep_kernel<<<grid, kThreads, kSmemBytes, cudaStreamPerThread>>>(tm_w, tm_x0, tm_x, tm_o, tm_s, x, dw, pw,
                                                                      pixels / kTilePx KNOB_ARG);
}
```

```cpp
#include <cuda_runtime.h>
#include <cuda_bf16.h>
#include <cuda.h>
#include <stdint.h>

namespace {

constexpr int kC = 384;
constexpr int kTilePx = 32;
constexpr int kStages = 5;
constexpr int kOutBufs = 8;
constexpr int kPark = 5;
constexpr int kThreads = 512;
constexpr int kStageBytes = kTilePx * kC * 2;
constexpr int kOutBytes = kTilePx * 192 * 2;
constexpr int kWChunkBytes = 64 * 192 * 2;
constexpr int kXSlabBytes = 64 * 128 * 2;
constexpr int kWOff = 2 * kStageBytes;
constexpr int kOutOff = kStages * kStageBytes;
constexpr int kDwOff = kOutOff + kOutBufs * kOutBytes;
constexpr int kFullOff = kDwOff + kC * 2;
constexpr int kEmptyOff = kFullOff + 8 * kStages;
constexpr int kOFullOff = kEmptyOff + 8 * kStages;
constexpr int kOEmptyOff = kOFullOff + 8 * kOutBufs;
constexpr int kWBarOff = kOEmptyOff + 8 * kOutBufs;
constexpr int kXBarOff = kWBarOff + 8 * 3;
constexpr int kDwBarOff = kXBarOff + 8 * 3;
constexpr int kSlotOff = kDwBarOff + 8;
constexpr int kOSlotOff = kSlotOff + 4 * kStages;
constexpr int kPSlotOff = kOSlotOff + 4 * kOutBufs;
constexpr int kPlanOff = kPSlotOff + 4 * kPark;
constexpr int kPullBarOff = (kPlanOff + 8 + 7) / 8 * 8;
constexpr int kPullOff = (kPullBarOff + 8 + 127) / 128 * 128;
constexpr int kPullBytes = kStageBytes / 8;
constexpr int kSmemBytes = kPullOff + kPullBytes + 1024;
static_assert(kWChunkBytes == kStageBytes && kWOff + 6 * kWChunkBytes <= kDwOff, "weight staging");
static_assert(kSmemBytes <= 232448, "shared memory");

struct Knobs {
    int first_gap;
    int pf_t0, pf_dt;
    int static_tiles;
    int park_from;
    int pull_to;
    int tile_clk, paced_to;
    int end_dt, end_step, end_tiles;
    int hold_pos[6], hold[6];
    int lead_pos[12], lead[12];
};
#define DEFAULT_KNOBS {436, 46, 834, 22, 3414, 526, 1224, 1400, 5447, 415, 7, \
    {412, 412, 562, 727, 1112, 4285}, {0, 2, 1, 2, 3, 1}, \
    {800, 1011, 1300, 1480, 1631, 2081, 2539, 2982, 3419, 3710, 4318, 4448}, {301, 419, 440, 519, 443, 329, 327, 177, -15, 210, 199, 153}}
#define KNOB_PARAM
#define KNOB_ARG
#define KNOB_DECL constexpr Knobs kn = DEFAULT_KNOBS;

struct Inputs { const char* p[3]; };
struct Globals {
    unsigned long long out_of_tiles;
    unsigned int tile_counter;
};
__device__ Globals g_globals;

__device__ __forceinline__ uint32_t smem_u32(const void* p) { return (uint32_t)__cvta_generic_to_shared(p); }

__device__ __forceinline__ void mbar_init(uint32_t bar, uint32_t cnt) {
    asm volatile("mbarrier.init.shared::cta.b64 [%0], %1;" ::"r"(bar), "r"(cnt) : "memory");
}
__device__ __forceinline__ void mbar_expect_tx(uint32_t bar, uint32_t bytes) {
    asm volatile("mbarrier.arrive.expect_tx.shared::cta.b64 _, [%0], %1;" ::"r"(bar), "r"(bytes) : "memory");
}
__device__ __forceinline__ void mbar_arrive(uint32_t bar) {
    asm volatile("mbarrier.arrive.shared::cta.b64 _, [%0];" ::"r"(bar) : "memory");
}
__device__ __forceinline__ void mbar_arrive_cluster(uint32_t bar) {
    asm volatile("mbarrier.arrive.shared::cluster.b64 _, [%0];" ::"r"(bar) : "memory");
}
__device__ __forceinline__ void mbar_wait(uint32_t bar, uint32_t parity) {
    asm volatile(
        "{\n.reg .pred p;\n.reg .u32 n;\n"
        "mbarrier.try_wait.parity.shared::cta.b64 p, [%0], %1;\n"
        "@p bra DONE;\n"
        "mov.u32 n, 0;\n"
        "LOOP:\n"
        "mbarrier.try_wait.parity.shared::cta.b64 p, [%0], %1;\n"
        "@p bra DONE;\n"
        "add.u32 n, n, 1;\n"
        "setp.lt.u32 p, n, 4194304;\n"
        "@p bra LOOP;\n"
        "trap;\n"
        "DONE:\n}" ::"r"(bar), "r"(parity) : "memory");
}
__device__ __forceinline__ bool mbar_try(uint32_t bar, uint32_t parity) {
    uint32_t ok;
    asm volatile("{\n.reg .pred p;\nmbarrier.try_wait.parity.shared::cta.b64 p, [%1], %2;\nselp.u32 %0, 1, 0, p;\n}"
                 : "=r"(ok) : "r"(bar), "r"(parity) : "memory");
    return ok;
}
__device__ __forceinline__ uint32_t map_to_cta(uint32_t addr, uint32_t cta) {
    uint32_t r;
    asm("mapa.shared::cluster.u32 %0, %1, %2;" : "=r"(r) : "r"(addr), "r"(cta));
    return r;
}
__device__ __forceinline__ void named_bar_sync(int id, int n) { asm volatile("bar.sync %0, %1;" ::"r"(id), "r"(n) : "memory"); }
__device__ __forceinline__ void named_bar_arrive(int id, int n) { asm volatile("bar.arrive %0, %1;" ::"r"(id), "r"(n) : "memory"); }
__device__ __forceinline__ void cluster_arrive() {
    __syncwarp();
    asm volatile("barrier.cluster.arrive.relaxed.aligned;" ::: "memory");
}
__device__ __forceinline__ void cluster_wait() {
    __syncwarp();
    asm volatile("barrier.cluster.wait.acquire.aligned;" ::: "memory");
}
__device__ __forceinline__ void prefetch_line(const void* p) { asm volatile("prefetch.global.L2 [%0];" ::"l"(p) : "memory"); }
__device__ __forceinline__ void prefetch_map(const CUtensorMap* m) { asm volatile("prefetch.tensormap [%0];" ::"l"(m) : "memory"); }
__device__ __forceinline__ uint32_t globaltimer() {
    uint32_t t;
    asm volatile("mov.u32 %0, %%globaltimer_lo;" : "=r"(t));
    return t;
}
__device__ __forceinline__ uint32_t clock32() {
    uint32_t t;
    asm volatile("mov.u32 %0, %%clock;" : "=r"(t));
    return t;
}
__device__ __forceinline__ int lds32(uint32_t addr) {
    int v;
    asm volatile("ld.shared.b32 %0, [%1];" : "=r"(v) : "r"(addr) : "memory");
    return v;
}
__device__ __forceinline__ int lds32_volatile(uint32_t addr) {
    int v;
    asm volatile("ld.volatile.shared.b32 %0, [%1];" : "=r"(v) : "r"(addr) : "memory");
    return v;
}
__device__ __forceinline__ uint32_t wait_nonzero(uint32_t addr) {
    uint32_t v;
    asm volatile(
        "{\n.reg .pred p;\n.reg .u32 n;\nmov.u32 n, 0;\n"
        "LOOP:\n"
        "ld.volatile.shared.b32 %0, [%1];\n"
        "setp.ne.u32 p, %0, 0;\n"
        "@p bra DONE;\n"
        "nanosleep.u32 20;\n"
        "add.u32 n, n, 1;\n"
        "setp.lt.u32 p, n, 4194304;\n"
        "@p bra LOOP;\n"
        "trap;\n"
        "DONE:\n}" : "=r"(v) : "r"(addr) : "memory");
    return v;
}
__device__ __forceinline__ void sts32(uint32_t addr, int v) { asm volatile("st.shared.b32 [%0], %1;" ::"r"(addr), "r"(v) : "memory"); }

#define ACC4(o) "+f"(d[o]), "+f"(d[o + 1]), "+f"(d[o + 2]), "+f"(d[o + 3])
#define ACC16(o) ACC4(o), ACC4(o + 4), ACC4(o + 8), ACC4(o + 12)
__device__ __forceinline__ void wgmma_rs(float (&d)[32], const uint32_t (&a)[4], uint64_t desc_b, int scale_d) {
    asm volatile(
        "{\n.reg .pred p;\nsetp.ne.b32 p, %37, 0;\n"
        "wgmma.mma_async.sync.aligned.m64n64k16.f32.bf16.bf16 "
        "{%0, %1, %2, %3, %4, %5, %6, %7, %8, %9, %10, %11, %12, %13, %14, %15, "
        "%16, %17, %18, %19, %20, %21, %22, %23, %24, %25, %26, %27, %28, %29, %30, %31}, "
        "{%32, %33, %34, %35}, %36, p, 1, 1, 0;\n}"
        : ACC16(0), ACC16(16)
        : "r"(a[0]), "r"(a[1]), "r"(a[2]), "r"(a[3]), "l"(desc_b), "r"(scale_d));
}
__device__ __forceinline__ void wgmma_rs(float (&d)[16], const uint32_t (&a)[4], uint64_t desc_b, int scale_d) {
    asm volatile(
        "{\n.reg .pred p;\nsetp.ne.b32 p, %21, 0;\n"
        "wgmma.mma_async.sync.aligned.m64n32k16.f32.bf16.bf16 "
        "{%0, %1, %2, %3, %4, %5, %6, %7, %8, %9, %10, %11, %12, %13, %14, %15}, "
        "{%16, %17, %18, %19}, %20, p, 1, 1, 0;\n}"
        : ACC16(0)
        : "r"(a[0]), "r"(a[1]), "r"(a[2]), "r"(a[3]), "l"(desc_b), "r"(scale_d));
}
__device__ __forceinline__ uint64_t make_desc(uint32_t addr, uint32_t group_stride) {
    return (uint64_t(1) << 62) | (uint64_t(group_stride >> 4) << 32) | (uint64_t(1) << 16) | (uint64_t)((addr & 0x3FFFF) >> 4);
}
__device__ __forceinline__ constexpr uint64_t desc_k(int k) { return (uint64_t)(((k >> 2) * 1024 + (k & 3) * 32) >> 4); }

__device__ __forceinline__ uint32_t pack_bf16(float lo, float hi) {
    uint32_t r;
    asm("cvt.rn.bf16x2.f32 %0, %1, %2;" : "=r"(r) : "f"(hi), "f"(lo));
    return r;
}
__device__ __forceinline__ uint32_t mul_bf16x2(uint32_t a, uint32_t b) {
    uint32_t r;
    asm("mul.rn.bf16x2 %0, %1, %2;" : "=r"(r) : "r"(a), "r"(b));
    return r;
}

__global__ void __cluster_dims__(2, 1, 1) __launch_bounds__(kThreads, 1)
dwsep_kernel(const __grid_constant__ Inputs in, Globals* __restrict__ globals, int num_tiles,
             const __grid_constant__ CUtensorMap tm_w, const __grid_constant__ CUtensorMap tm_x0,
             const __grid_constant__ CUtensorMap tm_x, const __grid_constant__ CUtensorMap tm_o,
             const __grid_constant__ CUtensorMap tm_s KNOB_PARAM) {
    KNOB_DECL
    extern __shared__ uint8_t smem_raw[];
    const uint32_t sb = (smem_u32(smem_raw) + 1023u) & ~1023u;

    uint32_t rank;
    asm("mov.u32 %0, %%cluster_ctarank;" : "=r"(rank));
    const int cluster = blockIdx.x >> 1;
    auto static_tile = [&](int i) { return (i >> 1) * gridDim.x + cluster * 2 + (i & 1); };

    if (threadIdx.x < 32) {
        prefetch_line(threadIdx.x < 18 ? in.p[2] + (blockIdx.x & 127) * 2304 + threadIdx.x * 128
                                       : in.p[1] + min(threadIdx.x - 18, 5) * 128);
    } else if (threadIdx.x < 224) {
        const uint32_t c0 = __shfl_sync(0xffffffffu, clock32(), 0), chunk = (threadIdx.x >> 5) - 1;
        const uint32_t delay = ((chunk >> 1) * gridDim.x + blockIdx.x) * kn.first_gap >> 7;
        for (int n = 0; clock32() - c0 < delay && n < 1024; n++) {}
        prefetch_line(in.p[0] + (size_t)blockIdx.x * kStageBytes + (threadIdx.x & 31) * 768 + chunk * 128);
    } else if (threadIdx.x == 288) {
        prefetch_map(&tm_w);
        prefetch_map(&tm_x0);
    }
    if (threadIdx.x >> 5 == 8) {
        if (threadIdx.x == 256) {
#pragma unroll
            for (int b = 0; b < 7; b++) mbar_init(sb + kWBarOff + 8 * b, 1);
            asm volatile("fence.proxy.async.shared::cta;" ::: "memory");
        }
        __syncwarp();
        named_bar_arrive(8, 384);
        if (threadIdx.x == 256) {
            mbar_expect_tx(sb + kDwBarOff, kC * 2);
            asm volatile("cp.async.bulk.shared::cluster.global.mbarrier::complete_tx::bytes [%0], [%1], %2, [%3];"
                         ::"r"(sb + kDwOff), "l"(in.p[1]), "r"(kC * 2), "r"(sb + kDwBarOff) : "memory");
#pragma unroll
            for (int j = 0; j < 3; j++) {
                mbar_expect_tx(sb + kWBarOff + 8 * j, 2 * kWChunkBytes);
#pragma unroll
                for (int c = 2 * j; c < 2 * j + 2; c++)
                    asm volatile("cp.async.bulk.tensor.3d.shared::cluster.global.mbarrier::complete_tx::bytes [%0], [%1, {%3, %4, %5}], [%2];"
                                 ::"r"(sb + kWOff + c * kWChunkBytes), "l"(&tm_w), "r"(sb + kWBarOff + 8 * j), "r"(0), "r"(c * 64),
                                   "r"((int)rank * 3) : "memory");
                mbar_expect_tx(sb + kXBarOff + 8 * j, kXSlabBytes);
                asm volatile("cp.async.bulk.tensor.4d.shared::cluster.global.mbarrier::complete_tx::bytes [%0], [%1, {%3, %3, %4, %5}], [%2];"
                             ::"r"(sb + j * kXSlabBytes), "l"(&tm_x0), "r"(sb + kXBarOff + 8 * j), "r"(0), "r"(2 * j),
                               "r"(cluster * 8) : "memory");
            }
        }
        __syncwarp();
    }

    if (threadIdx.x < 384) {
        asm volatile("setmaxnreg.inc.sync.aligned.u32 160;");
        cluster_arrive();
        if (threadIdx.x >> 5 != 8) named_bar_sync(8, 384);
        const int wg = __shfl_sync(0xffffffffu, threadIdx.x >> 7, 0);
        const int warp = (threadIdx.x >> 5) & 3;
        const int lane = threadIdx.x & 31;
        const int mi = lane >> 3, ri = lane & 7;
        const uint32_t leader_empty = map_to_cta(sb + kEmptyOff, 0);
        const uint32_t st_off = sb + kOutOff + (((mi >> 1) * 8 + ri) * 3 + wg) * 128 + (((2 * warp + (mi & 1)) ^ ((3 * ri + wg) & 7)) << 4);
        int s = 0, ob = 0;
        uint32_t ph = 0, oph = 1;
        auto release_stage = [&]() {
            if (lane == 0) mbar_arrive_cluster(leader_empty + 8 * s);
            if (++s == kStages) { s = 0; ph ^= 1; }
        };
        auto pack = [&](uint32_t (&p)[8], const float* acc) {
#pragma unroll
            for (int k = 0; k < 8; k++) p[k] = pack_bf16(acc[2 * k], acc[2 * k + 1]);
        };
        auto put = [&](const uint32_t (&p)[8], int t) {
            mbar_wait(sb + kOEmptyOff + 8 * ob, oph);
            if (threadIdx.x == 0) sts32(sb + kOSlotOff + 4 * ob, t);
#pragma unroll
            for (int q = 0; q < 2; q++)
                asm volatile("stmatrix.sync.aligned.m8n8.x4.trans.shared.b16 [%0], {%1, %2, %3, %4};"
                             ::"r"(st_off + ob * kOutBytes + q * (16 * 384)), "r"(p[4 * q]), "r"(p[4 * q + 1]),
                               "r"(p[4 * q + 2]), "r"(p[4 * q + 3]) : "memory");
            asm volatile("fence.proxy.async.shared::cta;" ::: "memory");
            __syncwarp();
            if (lane == 0) mbar_arrive(sb + kOFullOff + 8 * ob);
            if (++ob == kOutBufs) { ob = 0; oph ^= 1; }
        };
        auto my_turn = [&]() { named_bar_sync(2 + wg, 256); };
        auto pass_turn = [&]() { named_bar_arrive(wg == 2 ? 2 : 3 + wg, 256); };
        if (wg == 2) pass_turn();

        uint32_t a[24][4];
        {
            float acc0[32];
            uint32_t dws[48];
            mbar_wait(sb + kDwBarOff, 0);
#pragma unroll
            for (int k = 0; k < 48; k++) dws[k] = lds32(sb + kDwOff + k * 16 + (lane & 3) * 4);
            cluster_wait();
            const uint32_t wbase = sb + kWOff + wg * 8192 + ((mi >> 1) * 8 + ri) * 128 + (((2 * warp + (mi & 1)) ^ ri) << 4);
            const uint64_t desc = make_desc(sb, 2048);
#pragma unroll
            for (int j = 0; j < 3; j++) {
                mbar_wait(sb + kWBarOff + 8 * j, 0);
#pragma unroll
                for (int k = 8 * j; k < 8 * j + 8; k++) {
                    asm volatile("ldmatrix.sync.aligned.m8n8.x4.trans.shared.b16 {%0, %1, %2, %3}, [%4];"
                                 : "=r"(a[k][0]), "=r"(a[k][1]), "=r"(a[k][2]), "=r"(a[k][3])
                                 : "r"(wbase + (k >> 2) * kWChunkBytes + (k & 3) * 2048) : "memory");
                    a[k][0] = mul_bf16x2(a[k][0], dws[2 * k]);
                    a[k][1] = mul_bf16x2(a[k][1], dws[2 * k]);
                    a[k][2] = mul_bf16x2(a[k][2], dws[2 * k + 1]);
                    a[k][3] = mul_bf16x2(a[k][3], dws[2 * k + 1]);
                }
                if (lane >> 1 == j + 1 && lane < kStages) mbar_arrive_cluster(leader_empty + 8 * lane);
                if (j == 2) {
                    named_bar_arrive(wg == 0 ? 6 : 5, 384);
                    named_bar_arrive(wg == 2 ? 6 : 7, 384);
                }
                mbar_wait(sb + kXBarOff + 8 * j, 0);
                my_turn();
                asm volatile("wgmma.fence.sync.aligned;" ::: "memory");
#pragma unroll
                for (int k = 0; k < 8; k++) wgmma_rs(acc0, a[8 * j + k], desc + (j * kXSlabBytes >> 4) + desc_k(k), j + k != 0);
                pass_turn();
            }
            asm volatile("wgmma.commit_group.sync.aligned;" ::: "memory");
            named_bar_sync(5 + wg, 384);
            asm volatile("wgmma.wait_group.sync.aligned 0;" ::: "memory");
            release_stage();
            release_stage();
            uint32_t p[8];
            pack(p, acc0);
            put(p, static_tile(0));
            pack(p, acc0 + 16);
            put(p, static_tile(1));
        }

        float acc[16];
        uint32_t park[kPark][8];
        int parked = 0;
#pragma unroll
        for (int k = 0; k < kPark * 8; k++) asm volatile("mov.b32 %0, 0;" : "=r"(park[k / 8][k % 8]));
#pragma unroll 1
        while (true) {
            mbar_wait(sb + kFullOff + 8 * s, ph);
            const int t = lds32(sb + kSlotOff + 4 * s);
            if (t >= num_tiles) break;
            const uint64_t desc = make_desc(sb + s * kStageBytes, 6144);
            my_turn();
            asm volatile("wgmma.fence.sync.aligned;" ::: "memory");
#pragma unroll
            for (int k = 0; k < 24; k++) {
                if (k == 20) pass_turn();
                wgmma_rs(acc, a[k], desc + desc_k(k), k != 0);
            }
            asm volatile("wgmma.commit_group.sync.aligned;" ::: "memory");
            asm volatile("wgmma.wait_group.sync.aligned 0;" ::: "memory");
            release_stage();
            if (t >= kn.park_from && parked < kPark) {
#pragma unroll
                for (int k = 0; k < kPark; k++)
                    if (parked == k) pack(park[k], acc);
                if (threadIdx.x == 0) sts32(sb + kPSlotOff + 4 * parked, t);
                parked++;
            } else {
                uint32_t p[8];
                pack(p, acc);
                put(p, t);
            }
        }
#pragma unroll
        for (int k = 0; k < kPark; k++)
            if (k < parked) put(park[k], threadIdx.x == 0 ? lds32(sb + kPSlotOff + 4 * k) : 0);
    } else {
        asm volatile("setmaxnreg.dec.sync.aligned.u32 32;");
        const int role = (threadIdx.x >> 5) & 3;
        const bool lead = (threadIdx.x & 31) == 0;
        if (role >= 2) {
            const int par = role & 1;
            if (lead) {
                if (par == 0) {
#pragma unroll
                    for (int b = 0; b < kOutBufs; b++) {
                        mbar_init(sb + kOFullOff + 8 * b, 12);
                        mbar_init(sb + kOEmptyOff + 8 * b, 1);
                    }
                } else {
#pragma unroll
                    for (int s = 0; s < kStages; s++) {
                        mbar_init(sb + kFullOff + 8 * s, 1);
                        mbar_init(sb + kEmptyOff + 8 * s, 24);
                        if (s < 2) {
                            mbar_arrive(sb + kFullOff + 8 * s);
                            asm volatile("mbarrier.arrive.shared::cta.b64 _, [%0], 24;" ::"r"(sb + kEmptyOff + 8 * s) : "memory");
                        }
                    }
                    prefetch_map(&tm_x);
                    prefetch_map(&tm_o);
                    prefetch_map(&tm_s);
                }
                asm volatile("fence.mbarrier_init.release.cluster;" ::: "memory");
            }
            cluster_arrive();
            cluster_wait();
            if (lead) {
                uint64_t streaming;
                asm volatile("createpolicy.fractional.L2::evict_first.b64 %0, 1.0;" : "=l"(streaming));
                int head = par, tail = par, held = 0, pos = 0;
                int index = par, last;
                uint32_t ph = 0;
                auto advance = [&]() { if ((head += 2) >= kOutBufs) { head = par; ph ^= 1; } };
                auto issue = [&](bool hint) {
                    const int px = lds32(sb + kOSlotOff + 4 * tail) * kTilePx;
                    if (hint)
                        asm volatile("cp.async.bulk.tensor.3d.global.shared::cta.bulk_group.L2::cache_hint [%0, {%2, %3, %4}], [%1], %5;"
                                     ::"l"(&tm_o), "r"(sb + kOutOff + tail * kOutBytes), "r"(0), "r"((int)rank * 3), "r"(px), "l"(streaming) : "memory");
                    else
                        asm volatile("cp.async.bulk.tensor.3d.global.shared::cta.bulk_group [%0, {%2, %3, %4}], [%1];"
                                     ::"l"(&tm_o), "r"(sb + kOutOff + tail * kOutBytes), "r"(0), "r"((int)rank * 3), "r"(px) : "memory");
                    asm volatile("cp.async.bulk.commit_group;" ::: "memory");
                    if ((tail += 2) >= kOutBufs) tail = par;
                    index += 2;
                };
#pragma unroll 1
                while (true) {
                    bool got = false;
#pragma unroll 1
                    for (int q = 0; q < 1 << 22 && !got; q++) {
                        last = lds32_volatile(sb + kPlanOff);
                        if (last - index < kOutBufs) break;
                        got = mbar_try(sb + kOFullOff + 8 * head, ph);
                    }
                    if (!got) break;
                    pos = max(pos, lds32(sb + kOSlotOff + 4 * head));
                    held++;
                    advance();
                    int hold = 0;
#pragma unroll
                    for (int k = 0; k < 6; k++)
                        if (pos >= kn.hold_pos[k]) hold = kn.hold[k];
                    int freed = tail, n = 0;
#pragma unroll 1
                    for (; held > hold; held--, n++) issue(pos >= kn.hold_pos[5]);
#pragma unroll 1
                    while (n-- > 0) {
                        if (n == 0) asm volatile("cp.async.bulk.wait_group.read 0;" ::: "memory");
                        else if (n == 1) asm volatile("cp.async.bulk.wait_group.read 1;" ::: "memory");
                        else if (n == 2) asm volatile("cp.async.bulk.wait_group.read 2;" ::: "memory");
                        else asm volatile("cp.async.bulk.wait_group.read 3;" ::: "memory");
                        mbar_arrive(sb + kOEmptyOff + 8 * freed);
                        if ((freed += 2) >= kOutBufs) freed = par;
                    }
                }
#pragma unroll 1
                while (index <= last) {
                    if (held == 0) {
                        mbar_wait(sb + kOFullOff + 8 * head, ph);
                        advance();
                    } else {
                        held--;
                    }
                    const int left = last - index;
                    if (left < kn.end_tiles) {
                        const uint32_t due = wait_nonzero(sb + kPlanOff + 4) - left * kn.end_step;
                        for (int q = 0; (int)(globaltimer() - due) < 0 && q < 4096; q++) __nanosleep(20);
                    }
                    issue(false);
                }
                wait_nonzero(sb + kPlanOff + 4);
                asm volatile("cp.async.bulk.wait_group.read 0;" ::: "memory");
            }
        } else if (role == 1) {
            const uint32_t t_start = __shfl_sync(0xffffffffu, globaltimer(), 0);
            const uint32_t my_slot = sb + kSlotOff + 4 * min(threadIdx.x & 31, kStages - 1);
            sts32(my_slot, 0);
            sts32(sb + kPlanOff, 1 << 20);
            sts32(sb + kPlanOff + 4, 0);
            __threadfence_block();
            cluster_arrive();
            auto gate = [&](int t) {
                int p0 = 0, p1 = 1, l0 = kn.lead[0], l1 = kn.lead[0];
#pragma unroll
                for (int k = 0; k < 11; k++)
                    if (t >= kn.lead_pos[k]) { p0 = kn.lead_pos[k]; p1 = kn.lead_pos[k + 1]; l0 = kn.lead[k]; l1 = kn.lead[k + 1]; }
                const int half = gridDim.x >> 1;
                const int pos = t - l0 - (min(t, p1) - p0) * (l1 - l0) / (p1 - p0), i = (pos - half / 2) / half;
                if (pos <= half / 2) return 0;
                if (i >= kn.static_tiles) return pos;
                return (int)static_tile(i) | (pos - half / 2 - i * half) * kn.tile_clk / half << 16;
            };
            int gates = 0, round = 0;
#pragma unroll 1
            for (int t = blockIdx.x + gridDim.x; t < num_tiles; t += gridDim.x, round++) {
                if ((round & 31) == 1) gates = gate(t + (threadIdx.x & 31) * gridDim.x);
                if (t < kn.paced_to) {
                    const uint32_t due = kn.pf_t0 + (t - gridDim.x) * kn.pf_dt / gridDim.x;
                    for (int n = 0; globaltimer() - t_start < due && n < 4096; n++) __nanosleep(50);
                }
                const int g = __shfl_sync(0xffffffffu, gates, round + 31), need = g & 0xffff;
                uint32_t since = 0;
                for (int n = 0; n < 8192; n++) {
                    const int front = __reduce_max_sync(0xffffffffu, lds32_volatile(my_slot));
                    if (front > need) break;
                    if (front == need) {
                        const uint32_t now = __shfl_sync(0xffffffffu, clock32(), 0) | 1;
                        if (since == 0) since = now;
                        if (now - since >= g >> 16) break;
                    }
                    __nanosleep(30);
                }
                if (lead) {
                    if (t >= 2 * gridDim.x && t < kn.pull_to) {
                        asm volatile("mbarrier.expect_tx.relaxed.cta.shared::cta.b64 [%0], %1;" ::"r"(sb + kPullBarOff), "r"(kPullBytes) : "memory");
                        asm volatile("cp.async.bulk.tensor.2d.shared::cluster.global.mbarrier::complete_tx::bytes [%0], [%1, {%3, %4}], [%2];"
                                     ::"r"(sb + kPullOff), "l"(&tm_s), "r"(sb + kPullBarOff), "r"(0), "r"(t * (kStageBytes / 128)) : "memory");
                    } else {
                        asm volatile("cp.async.bulk.prefetch.L2.global [%0], %1;"
                                     ::"l"(in.p[0] + (size_t)t * kStageBytes), "r"(kStageBytes) : "memory");
                        if (t < 2 * gridDim.x) {
                            mbar_init(sb + kPullBarOff, 1);
                            asm volatile("fence.proxy.async.shared::cta;" ::: "memory");
                        }
                    }
                }
            }
            if (lead) {
                mbar_arrive(sb + kPullBarOff);
                mbar_wait(sb + kPullBarOff, 0);
            }
            cluster_wait();
        } else {
            cluster_arrive();
            cluster_wait();
            if (lead && rank == 0) {
                const uint32_t peer = map_to_cta(sb, 1);
                const int nstatic = kn.static_tiles * (gridDim.x >> 1);
                const unsigned last_fetch = num_tiles - nstatic + gridDim.x - 1;
                int s = 2, i = 2;
                uint32_t ph = 0;
                auto step = [&](unsigned& raw) -> bool {
                    const int t = nstatic + raw;
                    const bool valid = t < num_tiles;
                    raw = static_tile(i + 2) - nstatic;
                    if (i + 2 >= kn.static_tiles && valid)
                        asm volatile("atom.global.inc.u32 %0, [%1], %2;" : "+r"(raw) : "l"(&globals->tile_counter), "r"(last_fetch) : "memory");
                    mbar_wait(sb + kEmptyOff + 8 * s, ph);
                    const uint32_t full = kFullOff + 8 * s, slot = kSlotOff + 4 * s;
                    const uint32_t bytes = valid ? kStageBytes : 0;
                    sts32(sb + slot, t);
                    mbar_expect_tx(sb + full, bytes);
                    asm volatile("mbarrier.arrive.expect_tx.shared::cluster.b64 _, [%0], %1;" ::"r"(peer + full), "r"(bytes + 4) : "memory");
                    asm volatile("st.async.weak.shared::cluster.mbarrier::complete_tx::bytes.b32 [%0], %1, [%2];"
                                 ::"r"(peer + slot), "r"(t), "r"(peer + full) : "memory");
                    if (!valid) return false;
                    asm volatile(
                        "cp.async.bulk.tensor.4d.shared::cluster.global.mbarrier::complete_tx::bytes.multicast::cluster "
                        "[%0], [%1, {%3, %3, %3, %4}], [%2], %5;"
                        ::"r"(sb + s * kStageBytes), "l"(&tm_x), "r"(sb + full), "r"(0), "r"(t * (kTilePx / 8)),
                          "h"((uint16_t)3) : "memory");
                    if (++s == kStages) { s = 0; ph ^= 1; }
                    i++;
                    return true;
                };
                unsigned raw0 = static_tile(2) - nstatic, raw1 = static_tile(3) - nstatic;
#pragma unroll 1
                while (step(raw0) && step(raw1)) {}
                unsigned long long now;
                asm volatile("mov.u64 %0, %%globaltimer;" : "=l"(now));
                asm volatile("red.relaxed.gpu.global.max.u64 [%0], %1;" ::"l"(&globals->out_of_tiles), "l"(now) : "memory");
                sts32(sb + kPlanOff, i - 1);
                asm volatile("st.shared::cluster.b32 [%0], %1;" ::"r"(peer + kPlanOff), "r"(i - 1) : "memory");
#pragma unroll 1
                for (int k = 1; k < kStages; k++) {
                    if (++s == kStages) { s = 0; ph ^= 1; }
                    mbar_wait(sb + kEmptyOff + 8 * s, ph);
                    if (k == 2) {
                        asm volatile("ld.relaxed.gpu.global.u64 %0, [%1];" : "=l"(now) : "l"(&globals->out_of_tiles) : "memory");
                        const uint32_t end = ((uint32_t)now + kn.end_dt) | 1;
                        sts32(sb + kPlanOff + 4, end);
                        asm volatile("st.shared::cluster.b32 [%0], %1;" ::"r"(peer + kPlanOff + 4), "r"(end) : "memory");
                    }
                }
            }
        }
    }
}

typedef CUresult (*EncodeTiledFn)(CUtensorMap*, CUtensorMapDataType, cuuint32_t, void*, const cuuint64_t*,
                                  const cuuint64_t*, const cuuint32_t*, const cuuint32_t*, CUtensorMapInterleave,
                                  CUtensorMapSwizzle, CUtensorMapL2promotion, CUtensorMapFloatOOBfill);

}

extern "C" void kernel_launch(void* const* d_in, const int* in_sizes, int n_in, void* d_out, int out_size) {
    (void)n_in; (void)out_size;
    const __nv_bfloat16* x = (const __nv_bfloat16*)d_in[0];
    const __nv_bfloat16* dw = (const __nv_bfloat16*)d_in[1];
    const __nv_bfloat16* pw = (const __nv_bfloat16*)d_in[2];
    const int pixels = in_sizes[0] / kC;

    static EncodeTiledFn encode = nullptr;
    static int grid = 0;
    static Globals* globals = nullptr;
    if (!encode) {
        void* fn = nullptr;
        cudaDriverEntryPointQueryResult qr;
        cudaGetDriverEntryPoint("cuTensorMapEncodeTiled", &fn, cudaEnableDefault, &qr);
        encode = (EncodeTiledFn)fn;
        cudaGetSymbolAddress((void**)&globals, g_globals);
        cudaFuncSetAttribute(dwsep_kernel, cudaFuncAttributeMaxDynamicSharedMemorySize, kSmemBytes);
        int sms = 0, clusters = 0;
        cudaDeviceGetAttribute(&sms, cudaDevAttrMultiProcessorCount, 0);
        cudaLaunchConfig_t cfg = {};
        cudaLaunchAttribute attr = {};
        attr.id = cudaLaunchAttributeClusterDimension;
        attr.val.clusterDim.x = 2;
        attr.val.clusterDim.y = attr.val.clusterDim.z = 1;
        cfg.gridDim = dim3(sms & ~1);
        cfg.blockDim = dim3(kThreads);
        cfg.dynamicSmemBytes = kSmemBytes;
        cfg.attrs = &attr;
        cfg.numAttrs = 1;
        if (cudaOccupancyMaxActiveClusters(&clusters, dwsep_kernel, &cfg) != cudaSuccess || clusters < 1) {
            (void)cudaGetLastError();
            clusters = sms / 2;
        }
        grid = 2 * (clusters < sms / 2 ? clusters : sms / 2);
    }

    CUtensorMap tm_w, tm_x0, tm_x, tm_o, tm_s;
    auto make_map = [&](CUtensorMap* m, const void* base, int rank, const cuuint64_t* dims, const cuuint64_t* strides,
                        const cuuint32_t* box, CUtensorMapL2promotion promo,
                        CUtensorMapSwizzle swizzle = CU_TENSOR_MAP_SWIZZLE_128B) {
        const cuuint32_t ones[4] = {1, 1, 1, 1};
        encode(m, CU_TENSOR_MAP_DATA_TYPE_BFLOAT16, rank, (void*)base, dims, strides, box, ones,
               CU_TENSOR_MAP_INTERLEAVE_NONE, swizzle, promo, CU_TENSOR_MAP_FLOAT_OOB_FILL_NONE);
    };
    {
        const cuuint64_t dims[3] = {64, kC, 6}, strides[2] = {kC * 2, 128};
        const cuuint32_t box[3] = {64, 64, 3};
        make_map(&tm_w, pw, 3, dims, strides, box, CU_TENSOR_MAP_L2_PROMOTION_L2_128B);
    }
    {
        const cuuint64_t dims[4] = {64, 8, 6, (cuuint64_t)pixels / 8}, strides[3] = {kC * 2, 128, kC * 2 * 8};
        const cuuint32_t box0[4] = {64, 8, 2, 8}, box[4] = {64, 8, 6, kTilePx / 8};
        make_map(&tm_x0, x, 4, dims, strides, box0, CU_TENSOR_MAP_L2_PROMOTION_L2_128B);
        make_map(&tm_x, x, 4, dims, strides, box, CU_TENSOR_MAP_L2_PROMOTION_L2_128B);
    }
    {
        const cuuint64_t dims[2] = {8, (cuuint64_t)pixels * 6}, strides[1] = {128};
        const cuuint32_t box[2] = {8, kStageBytes / 128};
        make_map(&tm_s, x, 2, dims, strides, box, CU_TENSOR_MAP_L2_PROMOTION_L2_128B, CU_TENSOR_MAP_SWIZZLE_NONE);
    }
    {
        const cuuint64_t dims[3] = {64, 6, (cuuint64_t)pixels}, strides[2] = {128, kC * 2};
        const cuuint32_t box[3] = {64, 3, kTilePx};
        make_map(&tm_o, d_out, 3, dims, strides, box, CU_TENSOR_MAP_L2_PROMOTION_NONE);
    }
    dwsep_kernel<<<grid, kThreads, kSmemBytes, cudaStreamPerThread>>>(Inputs{{(const char*)x, (const char*)dw, (const char*)pw}}, globals, pixels / kTilePx, tm_w, tm_x0,
                                                                      tm_x, tm_o, tm_s KNOB_ARG);
}
```

```cpp
#include <cuda_runtime.h>
#include <cuda_bf16.h>
#include <cuda.h>
#include <stdint.h>

namespace {

constexpr int kC = 384;
constexpr int kTilePx = 32;
constexpr int kStages = 5;
constexpr int kOutBufs = 8;
constexpr int kPark = 5;
constexpr int kThreads = 512;
constexpr int kStageBytes = kTilePx * kC * 2;
constexpr int kOutBytes = kTilePx * 192 * 2;
constexpr int kWChunkBytes = 64 * 192 * 2;
constexpr int kXSlabBytes = 64 * 128 * 2;
constexpr int kWOff = 2 * kStageBytes;
constexpr int kOutOff = kStages * kStageBytes;
constexpr int kDwOff = kOutOff + kOutBufs * kOutBytes;
constexpr int kFullOff = kDwOff + kC * 2;
constexpr int kEmptyOff = kFullOff + 8 * kStages;
constexpr int kOFullOff = kEmptyOff + 8 * kStages;
constexpr int kOEmptyOff = kOFullOff + 8 * kOutBufs;
constexpr int kWBarOff = kOEmptyOff + 8 * kOutBufs;
constexpr int kXBarOff = kWBarOff + 8 * 3;
constexpr int kDwBarOff = kXBarOff + 8 * 3;
constexpr int kSlotOff = kDwBarOff + 8;
constexpr int kOSlotOff = kSlotOff + 4 * kStages;
constexpr int kPSlotOff = kOSlotOff + 4 * kOutBufs;
constexpr int kPlanOff = kPSlotOff + 4 * kPark;
constexpr int kPullBarOff = (kPlanOff + 8 + 7) / 8 * 8;
constexpr int kPullOff = (kPullBarOff + 8 + 127) / 128 * 128;
constexpr int kPullBytes = kStageBytes / 8;
constexpr int kSmemBytes = kPullOff + kPullBytes + 1024;
static_assert(kWChunkBytes == kStageBytes && kWOff + 6 * kWChunkBytes <= kDwOff, "weight staging");
static_assert(kSmemBytes <= 232448, "shared memory");

struct Knobs {
    int first_gap;
    int pf_t0, pf_dt;
    int static_tiles;
    int park_from;
    int pull_to;
    int slack, pace_pos[8], pace[8];
    int tile_ns, paced_to;
    int end_dt, end_step, end_tiles;
    int hold_pos[6], hold[6];
    int lead_pos[12], lead[12];
};
#define DEFAULT_KNOBS {436, 46, 839, 38, 3414, 497, 120, {1009, 1408, 1900, 2350, 2500, 2760, 3490, 3963}, {0, 889, 901, 900, 900, 877, 810, 793}, 690, 1400, 5631, 415, 7, \
    {340, 519, 560, 724, 1121, 4276}, {1, 3, 1, 2, 3, 1}, \
    {800, 1176, 1320, 1480, 1630, 2081, 2721, 3120, 3495, 3734, 4279, 4357}, {326, 381, 429, 498, 432, 302, 259, 235, 143, 164, 199, 175}}
#define KNOB_PARAM
#define KNOB_ARG
#define KNOB_DECL constexpr Knobs kn = DEFAULT_KNOBS;

struct Inputs { const char* p[3]; };
struct Globals {
    unsigned long long out_of_tiles;
    unsigned int tile_counter;
};
__device__ Globals g_globals;

__device__ __forceinline__ uint32_t smem_u32(const void* p) { return (uint32_t)__cvta_generic_to_shared(p); }

__device__ __forceinline__ void mbar_init(uint32_t bar, uint32_t cnt) {
    asm volatile("mbarrier.init.shared::cta.b64 [%0], %1;" ::"r"(bar), "r"(cnt) : "memory");
}
__device__ __forceinline__ void mbar_expect_tx(uint32_t bar, uint32_t bytes) {
    asm volatile("mbarrier.arrive.expect_tx.shared::cta.b64 _, [%0], %1;" ::"r"(bar), "r"(bytes) : "memory");
}
__device__ __forceinline__ void mbar_arrive(uint32_t bar) {
    asm volatile("mbarrier.arrive.shared::cta.b64 _, [%0];" ::"r"(bar) : "memory");
}
__device__ __forceinline__ void mbar_arrive_cluster(uint32_t bar) {
    asm volatile("mbarrier.arrive.shared::cluster.b64 _, [%0];" ::"r"(bar) : "memory");
}
__device__ __forceinline__ void mbar_wait(uint32_t bar, uint32_t parity) {
    asm volatile(
        "{\n.reg .pred p;\n.reg .u32 n;\n"
        "mbarrier.try_wait.parity.shared::cta.b64 p, [%0], %1;\n"
        "@p bra DONE;\n"
        "mov.u32 n, 0;\n"
        "LOOP:\n"
        "mbarrier.try_wait.parity.shared::cta.b64 p, [%0], %1;\n"
        "@p bra DONE;\n"
        "add.u32 n, n, 1;\n"
        "setp.lt.u32 p, n, 4194304;\n"
        "@p bra LOOP;\n"
        "trap;\n"
        "DONE:\n}" ::"r"(bar), "r"(parity) : "memory");
}
__device__ __forceinline__ bool mbar_try(uint32_t bar, uint32_t parity) {
    uint32_t ok;
    asm volatile("{\n.reg .pred p;\nmbarrier.try_wait.parity.shared::cta.b64 p, [%1], %2;\nselp.u32 %0, 1, 0, p;\n}"
                 : "=r"(ok) : "r"(bar), "r"(parity) : "memory");
    return ok;
}
__device__ __forceinline__ uint32_t map_to_cta(uint32_t addr, uint32_t cta) {
    uint32_t r;
    asm("mapa.shared::cluster.u32 %0, %1, %2;" : "=r"(r) : "r"(addr), "r"(cta));
    return r;
}
__device__ __forceinline__ void named_bar_sync(int id, int n) { asm volatile("bar.sync %0, %1;" ::"r"(id), "r"(n) : "memory"); }
__device__ __forceinline__ void named_bar_arrive(int id, int n) { asm volatile("bar.arrive %0, %1;" ::"r"(id), "r"(n) : "memory"); }
__device__ __forceinline__ void cluster_arrive() {
    __syncwarp();
    asm volatile("barrier.cluster.arrive.relaxed.aligned;" ::: "memory");
}
__device__ __forceinline__ void cluster_wait() {
    __syncwarp();
    asm volatile("barrier.cluster.wait.acquire.aligned;" ::: "memory");
}
__device__ __forceinline__ void prefetch_line(const void* p) { asm volatile("prefetch.global.L2 [%0];" ::"l"(p) : "memory"); }
__device__ __forceinline__ void prefetch_map(const CUtensorMap* m) { asm volatile("prefetch.tensormap [%0];" ::"l"(m) : "memory"); }
__device__ __forceinline__ uint32_t globaltimer() {
    uint32_t t;
    asm volatile("mov.u32 %0, %%globaltimer_lo;" : "=r"(t));
    return t;
}
__device__ __forceinline__ uint32_t clock32() {
    uint32_t t;
    asm volatile("mov.u32 %0, %%clock;" : "=r"(t));
    return t;
}
__device__ __forceinline__ int lds32(uint32_t addr) {
    int v;
    asm volatile("ld.shared.b32 %0, [%1];" : "=r"(v) : "r"(addr) : "memory");
    return v;
}
__device__ __forceinline__ int lds32_volatile(uint32_t addr) {
    int v;
    asm volatile("ld.volatile.shared.b32 %0, [%1];" : "=r"(v) : "r"(addr) : "memory");
    return v;
}
__device__ __forceinline__ uint32_t wait_nonzero(uint32_t addr) {
    uint32_t v;
    asm volatile(
        "{\n.reg .pred p;\n.reg .u32 n;\nmov.u32 n, 0;\n"
        "LOOP:\n"
        "ld.volatile.shared.b32 %0, [%1];\n"
        "setp.ne.u32 p, %0, 0;\n"
        "@p bra DONE;\n"
        "nanosleep.u32 20;\n"
        "add.u32 n, n, 1;\n"
        "setp.lt.u32 p, n, 4194304;\n"
        "@p bra LOOP;\n"
        "trap;\n"
        "DONE:\n}" : "=r"(v) : "r"(addr) : "memory");
    return v;
}
__device__ __forceinline__ void sts32(uint32_t addr, int v) { asm volatile("st.shared.b32 [%0], %1;" ::"r"(addr), "r"(v) : "memory"); }

#define ACC4(o) "+f"(d[o]), "+f"(d[o + 1]), "+f"(d[o + 2]), "+f"(d[o + 3])
#define ACC16(o) ACC4(o), ACC4(o + 4), ACC4(o + 8), ACC4(o + 12)
__device__ __forceinline__ void wgmma_rs(float (&d)[32], const uint32_t (&a)[4], uint64_t desc_b, int scale_d) {
    asm volatile(
        "{\n.reg .pred p;\nsetp.ne.b32 p, %37, 0;\n"
        "wgmma.mma_async.sync.aligned.m64n64k16.f32.bf16.bf16 "
        "{%0, %1, %2, %3, %4, %5, %6, %7, %8, %9, %10, %11, %12, %13, %14, %15, "
        "%16, %17, %18, %19, %20, %21, %22, %23, %24, %25, %26, %27, %28, %29, %30, %31}, "
        "{%32, %33, %34, %35}, %36, p, 1, 1, 0;\n}"
        : ACC16(0), ACC16(16)
        : "r"(a[0]), "r"(a[1]), "r"(a[2]), "r"(a[3]), "l"(desc_b), "r"(scale_d));
}
__device__ __forceinline__ void wgmma_rs(float (&d)[16], const uint32_t (&a)[4], uint64_t desc_b, int scale_d) {
    asm volatile(
        "{\n.reg .pred p;\nsetp.ne.b32 p, %21, 0;\n"
        "wgmma.mma_async.sync.aligned.m64n32k16.f32.bf16.bf16 "
        "{%0, %1, %2, %3, %4, %5, %6, %7, %8, %9, %10, %11, %12, %13, %14, %15}, "
        "{%16, %17, %18, %19}, %20, p, 1, 1, 0;\n}"
        : ACC16(0)
        : "r"(a[0]), "r"(a[1]), "r"(a[2]), "r"(a[3]), "l"(desc_b), "r"(scale_d));
}
__device__ __forceinline__ uint64_t make_desc(uint32_t addr, uint32_t group_stride) {
    return (uint64_t(1) << 62) | (uint64_t(group_stride >> 4) << 32) | (uint64_t(1) << 16) | (uint64_t)((addr & 0x3FFFF) >> 4);
}
__device__ __forceinline__ constexpr uint64_t desc_k(int k) { return (uint64_t)(((k >> 2) * 1024 + (k & 3) * 32) >> 4); }

__device__ __forceinline__ uint32_t pack_bf16(float lo, float hi) {
    uint32_t r;
    asm("cvt.rn.bf16x2.f32 %0, %1, %2;" : "=r"(r) : "f"(hi), "f"(lo));
    return r;
}
__device__ __forceinline__ uint32_t mul_bf16x2(uint32_t a, uint32_t b) {
    uint32_t r;
    asm("mul.rn.bf16x2 %0, %1, %2;" : "=r"(r) : "r"(a), "r"(b));
    return r;
}

__global__ void __cluster_dims__(2, 1, 1) __launch_bounds__(kThreads, 1)
dwsep_kernel(const __grid_constant__ Inputs in, Globals* __restrict__ globals, int num_tiles,
             const __grid_constant__ CUtensorMap tm_w, const __grid_constant__ CUtensorMap tm_x0,
             const __grid_constant__ CUtensorMap tm_x, const __grid_constant__ CUtensorMap tm_o,
             const __grid_constant__ CUtensorMap tm_s KNOB_PARAM) {
    KNOB_DECL
    extern __shared__ uint8_t smem_raw[];
    const uint32_t sb = (smem_u32(smem_raw) + 1023u) & ~1023u;

    uint32_t rank;
    asm("mov.u32 %0, %%cluster_ctarank;" : "=r"(rank));
    const int cluster = blockIdx.x >> 1;
    auto static_tile = [&](int i) { return (i >> 1) * gridDim.x + cluster * 2 + (i & 1); };

    auto period = [&](int t) {
        int d = 0;
#pragma unroll
        for (int k = 0; k < 8; k++)
            if (t >= kn.pace_pos[k]) d = kn.pace[k];
        return d;
    };

    if (threadIdx.x < 32) {
        prefetch_line(threadIdx.x < 18 ? in.p[2] + (blockIdx.x & 127) * 2304 + threadIdx.x * 128
                                       : in.p[1] + min(threadIdx.x - 18, 5) * 128);
    } else if (threadIdx.x < 224) {
        const uint32_t c0 = __shfl_sync(0xffffffffu, clock32(), 0), chunk = (threadIdx.x >> 5) - 1;
        const uint32_t delay = ((chunk >> 1) * gridDim.x + blockIdx.x) * kn.first_gap >> 7;
        for (int n = 0; clock32() - c0 < delay && n < 1024; n++) {}
        prefetch_line(in.p[0] + (size_t)blockIdx.x * kStageBytes + (threadIdx.x & 31) * 768 + chunk * 128);
    } else if (threadIdx.x == 288) {
        prefetch_map(&tm_w);
        prefetch_map(&tm_x0);
    }
    if (threadIdx.x >> 5 == 8) {
        if (threadIdx.x == 256) {
#pragma unroll
            for (int b = 0; b < 7; b++) mbar_init(sb + kWBarOff + 8 * b, 1);
            asm volatile("fence.proxy.async.shared::cta;" ::: "memory");
        }
        __syncwarp();
        named_bar_arrive(8, 384);
        if (threadIdx.x == 256) {
            mbar_expect_tx(sb + kDwBarOff, kC * 2);
            asm volatile("cp.async.bulk.shared::cluster.global.mbarrier::complete_tx::bytes [%0], [%1], %2, [%3];"
                         ::"r"(sb + kDwOff), "l"(in.p[1]), "r"(kC * 2), "r"(sb + kDwBarOff) : "memory");
#pragma unroll
            for (int j = 0; j < 3; j++) {
                mbar_expect_tx(sb + kWBarOff + 8 * j, 2 * kWChunkBytes);
#pragma unroll
                for (int c = 2 * j; c < 2 * j + 2; c++)
                    asm volatile("cp.async.bulk.tensor.3d.shared::cluster.global.mbarrier::complete_tx::bytes [%0], [%1, {%3, %4, %5}], [%2];"
                                 ::"r"(sb + kWOff + c * kWChunkBytes), "l"(&tm_w), "r"(sb + kWBarOff + 8 * j), "r"(0), "r"(c * 64),
                                   "r"((int)rank * 3) : "memory");
                mbar_expect_tx(sb + kXBarOff + 8 * j, kXSlabBytes);
                asm volatile("cp.async.bulk.tensor.4d.shared::cluster.global.mbarrier::complete_tx::bytes [%0], [%1, {%3, %3, %4, %5}], [%2];"
                             ::"r"(sb + j * kXSlabBytes), "l"(&tm_x0), "r"(sb + kXBarOff + 8 * j), "r"(0), "r"(2 * j),
                               "r"(cluster * 8) : "memory");
            }
        }
        __syncwarp();
    }

    if (threadIdx.x < 384) {
        asm volatile("setmaxnreg.inc.sync.aligned.u32 160;");
        cluster_arrive();
        if (threadIdx.x >> 5 != 8) named_bar_sync(8, 384);
        const int wg = __shfl_sync(0xffffffffu, threadIdx.x >> 7, 0);
        const int warp = (threadIdx.x >> 5) & 3;
        const int lane = threadIdx.x & 31;
        const int mi = lane >> 3, ri = lane & 7;
        const uint32_t leader_empty = map_to_cta(sb + kEmptyOff, 0);
        const uint32_t st_off = sb + kOutOff + (((mi >> 1) * 8 + ri) * 3 + wg) * 128 + (((2 * warp + (mi & 1)) ^ ((3 * ri + wg) & 7)) << 4);
        int s = 0, ob = 0;
        uint32_t ph = 0, oph = 1;
        auto release_stage = [&]() {
            if (lane == 0) mbar_arrive_cluster(leader_empty + 8 * s);
            if (++s == kStages) { s = 0; ph ^= 1; }
        };
        auto pack = [&](uint32_t (&p)[8], const float* acc) {
#pragma unroll
            for (int k = 0; k < 8; k++) p[k] = pack_bf16(acc[2 * k], acc[2 * k + 1]);
        };
        auto put = [&](const uint32_t (&p)[8], int t) {
            mbar_wait(sb + kOEmptyOff + 8 * ob, oph);
            if (threadIdx.x == 0) sts32(sb + kOSlotOff + 4 * ob, t);
#pragma unroll
            for (int q = 0; q < 2; q++)
                asm volatile("stmatrix.sync.aligned.m8n8.x4.trans.shared.b16 [%0], {%1, %2, %3, %4};"
                             ::"r"(st_off + ob * kOutBytes + q * (16 * 384)), "r"(p[4 * q]), "r"(p[4 * q + 1]),
                               "r"(p[4 * q + 2]), "r"(p[4 * q + 3]) : "memory");
            asm volatile("fence.proxy.async.shared::cta;" ::: "memory");
            __syncwarp();
            if (lane == 0) mbar_arrive(sb + kOFullOff + 8 * ob);
            if (++ob == kOutBufs) { ob = 0; oph ^= 1; }
        };
        auto my_turn = [&]() { named_bar_sync(2 + wg, 256); };
        auto pass_turn = [&]() { named_bar_arrive(wg == 2 ? 2 : 3 + wg, 256); };
        if (wg == 2) pass_turn();

        uint32_t a[24][4];
        {
            float acc0[32];
            uint32_t dws[48];
            mbar_wait(sb + kDwBarOff, 0);
#pragma unroll
            for (int k = 0; k < 48; k++) dws[k] = lds32(sb + kDwOff + k * 16 + (lane & 3) * 4);
            cluster_wait();
            const uint32_t wbase = sb + kWOff + wg * 8192 + ((mi >> 1) * 8 + ri) * 128 + (((2 * warp + (mi & 1)) ^ ri) << 4);
            const uint64_t desc = make_desc(sb, 2048);
#pragma unroll
            for (int j = 0; j < 3; j++) {
                mbar_wait(sb + kWBarOff + 8 * j, 0);
#pragma unroll
                for (int k = 8 * j; k < 8 * j + 8; k++) {
                    asm volatile("ldmatrix.sync.aligned.m8n8.x4.trans.shared.b16 {%0, %1, %2, %3}, [%4];"
                                 : "=r"(a[k][0]), "=r"(a[k][1]), "=r"(a[k][2]), "=r"(a[k][3])
                                 : "r"(wbase + (k >> 2) * kWChunkBytes + (k & 3) * 2048) : "memory");
                    a[k][0] = mul_bf16x2(a[k][0], dws[2 * k]);
                    a[k][1] = mul_bf16x2(a[k][1], dws[2 * k]);
                    a[k][2] = mul_bf16x2(a[k][2], dws[2 * k + 1]);
                    a[k][3] = mul_bf16x2(a[k][3], dws[2 * k + 1]);
                }
                if (lane >> 1 == j + 1 && lane < kStages) mbar_arrive_cluster(leader_empty + 8 * lane);
                if (j == 2) {
                    named_bar_arrive(wg == 0 ? 6 : 5, 384);
                    named_bar_arrive(wg == 2 ? 6 : 7, 384);
                }
                mbar_wait(sb + kXBarOff + 8 * j, 0);
                my_turn();
                asm volatile("wgmma.fence.sync.aligned;" ::: "memory");
#pragma unroll
                for (int k = 0; k < 8; k++) wgmma_rs(acc0, a[8 * j + k], desc + (j * kXSlabBytes >> 4) + desc_k(k), j + k != 0);
                pass_turn();
            }
            asm volatile("wgmma.commit_group.sync.aligned;" ::: "memory");
            named_bar_sync(5 + wg, 384);
            asm volatile("wgmma.wait_group.sync.aligned 0;" ::: "memory");
            release_stage();
            release_stage();
            uint32_t p[8];
            pack(p, acc0);
            put(p, static_tile(0));
            pack(p, acc0 + 16);
            put(p, static_tile(1));
        }

        float acc[16];
        uint32_t park[kPark][8];
        int parked = 0;
        uint32_t next = __shfl_sync(0xffffffffu, globaltimer(), 0);
#pragma unroll
        for (int k = 0; k < kPark * 8; k++) asm volatile("mov.b32 %0, 0;" : "=r"(park[k / 8][k % 8]));
#pragma unroll 1
        while (true) {
            mbar_wait(sb + kFullOff + 8 * s, ph);
            const int slot = lds32(sb + kSlotOff + 4 * s), t = slot >> 12;
            if (t >= num_tiles) break;
            const uint64_t desc = make_desc(sb + s * kStageBytes, 6144);
            if (wg == 0 && (slot & 4095) != 0) {
                uint32_t now = __shfl_sync(0xffffffffu, globaltimer(), 0);
                for (int n = 0; (int)(now - next) < 0 && n < 256; n++) now = __shfl_sync(0xffffffffu, globaltimer(), 0);
                if ((int)(now - next) > kn.slack) next = now - kn.slack;
                next += slot & 4095;
            }
            my_turn();
            asm volatile("wgmma.fence.sync.aligned;" ::: "memory");
#pragma unroll
            for (int k = 0; k < 24; k++) {
                if (k == 20) pass_turn();
                wgmma_rs(acc, a[k], desc + desc_k(k), k != 0);
            }
            asm volatile("wgmma.commit_group.sync.aligned;" ::: "memory");
            asm volatile("wgmma.wait_group.sync.aligned 0;" ::: "memory");
            release_stage();
            if (t >= kn.park_from && parked < kPark) {
#pragma unroll
                for (int k = 0; k < kPark; k++)
                    if (parked == k) pack(park[k], acc);
                if (threadIdx.x == 0) sts32(sb + kPSlotOff + 4 * parked, t);
                parked++;
            } else {
                uint32_t p[8];
                pack(p, acc);
                put(p, t);
            }
        }
#pragma unroll
        for (int k = 0; k < kPark; k++)
            if (k < parked) put(park[k], threadIdx.x == 0 ? lds32(sb + kPSlotOff + 4 * k) : 0);
    } else {
        asm volatile("setmaxnreg.dec.sync.aligned.u32 32;");
        const int role = (threadIdx.x >> 5) & 3;
        const bool lead = (threadIdx.x & 31) == 0;
        if (role >= 2) {
            const int par = role & 1;
            if (lead) {
                if (par == 0) {
#pragma unroll
                    for (int b = 0; b < kOutBufs; b++) {
                        mbar_init(sb + kOFullOff + 8 * b, 12);
                        mbar_init(sb + kOEmptyOff + 8 * b, 1);
                    }
                } else {
#pragma unroll
                    for (int s = 0; s < kStages; s++) {
                        mbar_init(sb + kFullOff + 8 * s, 1);
                        mbar_init(sb + kEmptyOff + 8 * s, 24);
                        if (s < 2) {
                            mbar_arrive(sb + kFullOff + 8 * s);
                            asm volatile("mbarrier.arrive.shared::cta.b64 _, [%0], 24;" ::"r"(sb + kEmptyOff + 8 * s) : "memory");
                        }
                    }
                    prefetch_map(&tm_x);
                    prefetch_map(&tm_o);
                    prefetch_map(&tm_s);
                }
                asm volatile("fence.mbarrier_init.release.cluster;" ::: "memory");
            }
            cluster_arrive();
            cluster_wait();
            if (lead) {
                uint64_t streaming;
                asm volatile("createpolicy.fractional.L2::evict_first.b64 %0, 1.0;" : "=l"(streaming));
                int head = par, tail = par, held = 0, pos = 0;
                int index = par, last;
                uint32_t ph = 0;
                auto advance = [&]() { if ((head += 2) >= kOutBufs) { head = par; ph ^= 1; } };
                auto issue = [&](bool hint) {
                    const int px = lds32(sb + kOSlotOff + 4 * tail) * kTilePx;
                    if (hint)
                        asm volatile("cp.async.bulk.tensor.3d.global.shared::cta.bulk_group.L2::cache_hint [%0, {%2, %3, %4}], [%1], %5;"
                                     ::"l"(&tm_o), "r"(sb + kOutOff + tail * kOutBytes), "r"(0), "r"((int)rank * 3), "r"(px), "l"(streaming) : "memory");
                    else
                        asm volatile("cp.async.bulk.tensor.3d.global.shared::cta.bulk_group [%0, {%2, %3, %4}], [%1];"
                                     ::"l"(&tm_o), "r"(sb + kOutOff + tail * kOutBytes), "r"(0), "r"((int)rank * 3), "r"(px) : "memory");
                    asm volatile("cp.async.bulk.commit_group;" ::: "memory");
                    if ((tail += 2) >= kOutBufs) tail = par;
                    index += 2;
                };
#pragma unroll 1
                while (true) {
                    bool got = false;
#pragma unroll 1
                    for (int q = 0; q < 1 << 22 && !got; q++) {
                        last = lds32_volatile(sb + kPlanOff);
                        if (last - index < kOutBufs) break;
                        got = mbar_try(sb + kOFullOff + 8 * head, ph);
                    }
                    if (!got) break;
                    pos = max(pos, lds32(sb + kOSlotOff + 4 * head));
                    held++;
                    advance();
                    int hold = 0;
#pragma unroll
                    for (int k = 0; k < 6; k++)
                        if (pos >= kn.hold_pos[k]) hold = kn.hold[k];
                    int freed = tail, n = 0;
#pragma unroll 1
                    for (; held > hold; held--, n++) issue(pos >= kn.hold_pos[5]);
#pragma unroll 1
                    while (n-- > 0) {
                        if (n == 0) asm volatile("cp.async.bulk.wait_group.read 0;" ::: "memory");
                        else if (n == 1) asm volatile("cp.async.bulk.wait_group.read 1;" ::: "memory");
                        else if (n == 2) asm volatile("cp.async.bulk.wait_group.read 2;" ::: "memory");
                        else asm volatile("cp.async.bulk.wait_group.read 3;" ::: "memory");
                        mbar_arrive(sb + kOEmptyOff + 8 * freed);
                        if ((freed += 2) >= kOutBufs) freed = par;
                    }
                }
#pragma unroll 1
                while (index <= last) {
                    if (held == 0) {
                        mbar_wait(sb + kOFullOff + 8 * head, ph);
                        advance();
                    } else {
                        held--;
                    }
                    const int left = last - index;
                    if (left < kn.end_tiles) {
                        const uint32_t due = wait_nonzero(sb + kPlanOff + 4) - left * kn.end_step;
                        for (int q = 0; (int)(globaltimer() - due) < 0 && q < 4096; q++) __nanosleep(20);
                    }
                    issue(false);
                }
                wait_nonzero(sb + kPlanOff + 4);
                asm volatile("cp.async.bulk.wait_group.read 0;" ::: "memory");
            }
        } else if (role == 1) {
            const uint32_t t_start = __shfl_sync(0xffffffffu, globaltimer(), 0);
            const uint32_t my_slot = sb + kSlotOff + 4 * min(threadIdx.x & 31, kStages - 1);
            sts32(my_slot, 0);
            sts32(sb + kPlanOff, 1 << 20);
            sts32(sb + kPlanOff + 4, 0);
            __threadfence_block();
            cluster_arrive();
            auto gate = [&](int t) {
                int p0 = 0, p1 = 1, l0 = kn.lead[0], l1 = kn.lead[0];
#pragma unroll
                for (int k = 0; k < 11; k++)
                    if (t >= kn.lead_pos[k]) { p0 = kn.lead_pos[k]; p1 = kn.lead_pos[k + 1]; l0 = kn.lead[k]; l1 = kn.lead[k + 1]; }
                const int half = gridDim.x >> 1;
                const int pos = t - l0 - (min(t, p1) - p0) * (l1 - l0) / (p1 - p0), i = (pos - half / 2) / half;
                if (pos <= half / 2) return 0;
                if (i >= kn.static_tiles) return pos;
                return (int)static_tile(i) | (pos - half / 2 - i * half) * max(kn.tile_ns, period(pos - 4 * half)) / half << 16;
            };
            int gates = 0, round = 0;
#pragma unroll 1
            for (int t = blockIdx.x + gridDim.x; t < num_tiles; t += gridDim.x, round++) {
                if ((round & 31) == 1) gates = gate(t + (threadIdx.x & 31) * gridDim.x);
                if (t < kn.paced_to) {
                    const uint32_t due = kn.pf_t0 + (t - gridDim.x) * kn.pf_dt / gridDim.x;
                    for (int n = 0; globaltimer() - t_start < due && n < 4096; n++) __nanosleep(50);
                }
                const int g = __shfl_sync(0xffffffffu, gates, round + 31), need = g & 0xffff;
                uint32_t since = 0;
                for (int n = 0; n < 8192; n++) {
                    const int front = __reduce_max_sync(0xffffffffu, lds32_volatile(my_slot)) >> 12;
                    if (front > need) break;
                    if (front == need) {
                        const uint32_t now = __shfl_sync(0xffffffffu, globaltimer(), 0) | 1;
                        if (since == 0) since = now;
                        if (now - since >= g >> 16) break;
                    }
                    __nanosleep(30);
                }
                if (lead) {
                    if (t >= 2 * gridDim.x && t < kn.pull_to) {
                        asm volatile("mbarrier.expect_tx.relaxed.cta.shared::cta.b64 [%0], %1;" ::"r"(sb + kPullBarOff), "r"(kPullBytes) : "memory");
                        asm volatile("cp.async.bulk.tensor.2d.shared::cluster.global.mbarrier::complete_tx::bytes [%0], [%1, {%3, %4}], [%2];"
                                     ::"r"(sb + kPullOff), "l"(&tm_s), "r"(sb + kPullBarOff), "r"(0), "r"(t * (kStageBytes / 128)) : "memory");
                    } else {
                        asm volatile("cp.async.bulk.prefetch.L2.global [%0], %1;"
                                     ::"l"(in.p[0] + (size_t)t * kStageBytes), "r"(kStageBytes) : "memory");
                        if (t < 2 * gridDim.x) {
                            mbar_init(sb + kPullBarOff, 1);
                            asm volatile("fence.proxy.async.shared::cta;" ::: "memory");
                        }
                    }
                }
            }
            if (lead) {
                mbar_arrive(sb + kPullBarOff);
                mbar_wait(sb + kPullBarOff, 0);
            }
            cluster_wait();
        } else {
            cluster_arrive();
            cluster_wait();
            if (lead && rank == 0) {
                const uint32_t peer = map_to_cta(sb, 1);
                const int nstatic = kn.static_tiles * (gridDim.x >> 1);
                const unsigned last_fetch = num_tiles - nstatic + gridDim.x - 1;
                int s = 2, i = 2;
                uint32_t ph = 0;
                auto step = [&](unsigned& raw) -> bool {
                    const int t = nstatic + raw;
                    const bool valid = t < num_tiles;
                    raw = static_tile(i + 2) - nstatic;
                    if (i + 2 >= kn.static_tiles && valid)
                        asm volatile("atom.global.inc.u32 %0, [%1], %2;" : "+r"(raw) : "l"(&globals->tile_counter), "r"(last_fetch) : "memory");
                    const int word = t << 12 | period(t);
                    mbar_wait(sb + kEmptyOff + 8 * s, ph);
                    const uint32_t full = kFullOff + 8 * s, slot = kSlotOff + 4 * s;
                    const uint32_t bytes = valid ? kStageBytes : 0;
                    sts32(sb + slot, word);
                    mbar_expect_tx(sb + full, bytes);
                    asm volatile("mbarrier.arrive.expect_tx.shared::cluster.b64 _, [%0], %1;" ::"r"(peer + full), "r"(bytes + 4) : "memory");
                    asm volatile("st.async.weak.shared::cluster.mbarrier::complete_tx::bytes.b32 [%0], %1, [%2];"
                                 ::"r"(peer + slot), "r"(word), "r"(peer + full) : "memory");
                    if (!valid) return false;
                    asm volatile(
                        "cp.async.bulk.tensor.4d.shared::cluster.global.mbarrier::complete_tx::bytes.multicast::cluster "
                        "[%0], [%1, {%3, %3, %3, %4}], [%2], %5;"
                        ::"r"(sb + s * kStageBytes), "l"(&tm_x), "r"(sb + full), "r"(0), "r"(t * (kTilePx / 8)),
                          "h"((uint16_t)3) : "memory");
                    if (++s == kStages) { s = 0; ph ^= 1; }
                    i++;
                    return true;
                };
                unsigned raw0 = static_tile(2) - nstatic, raw1 = static_tile(3) - nstatic;
#pragma unroll 1
                while (step(raw0) && step(raw1)) {}
                unsigned long long now;
                asm volatile("mov.u64 %0, %%globaltimer;" : "=l"(now));
                asm volatile("red.relaxed.gpu.global.max.u64 [%0], %1;" ::"l"(&globals->out_of_tiles), "l"(now) : "memory");
                sts32(sb + kPlanOff, i - 1);
                asm volatile("st.shared::cluster.b32 [%0], %1;" ::"r"(peer + kPlanOff), "r"(i - 1) : "memory");
#pragma unroll 1
                for (int k = 1; k < kStages; k++) {
                    if (++s == kStages) { s = 0; ph ^= 1; }
                    mbar_wait(sb + kEmptyOff + 8 * s, ph);
                    if (k == 2) {
                        asm volatile("ld.relaxed.gpu.global.u64 %0, [%1];" : "=l"(now) : "l"(&globals->out_of_tiles) : "memory");
                        const uint32_t end = ((uint32_t)now + kn.end_dt) | 1;
                        sts32(sb + kPlanOff + 4, end);
                        asm volatile("st.shared::cluster.b32 [%0], %1;" ::"r"(peer + kPlanOff + 4), "r"(end) : "memory");
                    }
                }
            }
        }
    }
}

typedef CUresult (*EncodeTiledFn)(CUtensorMap*, CUtensorMapDataType, cuuint32_t, void*, const cuuint64_t*,
                                  const cuuint64_t*, const cuuint32_t*, const cuuint32_t*, CUtensorMapInterleave,
                                  CUtensorMapSwizzle, CUtensorMapL2promotion, CUtensorMapFloatOOBfill);

}

extern "C" void kernel_launch(void* const* d_in, const int* in_sizes, int n_in, void* d_out, int out_size) {
    (void)n_in; (void)out_size;
    const __nv_bfloat16* x = (const __nv_bfloat16*)d_in[0];
    const __nv_bfloat16* dw = (const __nv_bfloat16*)d_in[1];
    const __nv_bfloat16* pw = (const __nv_bfloat16*)d_in[2];
    const int pixels = in_sizes[0] / kC;

    static EncodeTiledFn encode = nullptr;
    static int grid = 0;
    static Globals* globals = nullptr;
    if (!encode) {
        void* fn = nullptr;
        cudaDriverEntryPointQueryResult qr;
        cudaGetDriverEntryPoint("cuTensorMapEncodeTiled", &fn, cudaEnableDefault, &qr);
        encode = (EncodeTiledFn)fn;
        cudaGetSymbolAddress((void**)&globals, g_globals);
        cudaFuncSetAttribute(dwsep_kernel, cudaFuncAttributeMaxDynamicSharedMemorySize, kSmemBytes);
        int sms = 0, clusters = 0;
        cudaDeviceGetAttribute(&sms, cudaDevAttrMultiProcessorCount, 0);
        cudaLaunchConfig_t cfg = {};
        cudaLaunchAttribute attr = {};
        attr.id = cudaLaunchAttributeClusterDimension;
        attr.val.clusterDim.x = 2;
        attr.val.clusterDim.y = attr.val.clusterDim.z = 1;
        cfg.gridDim = dim3(sms & ~1);
        cfg.blockDim = dim3(kThreads);
        cfg.dynamicSmemBytes = kSmemBytes;
        cfg.attrs = &attr;
        cfg.numAttrs = 1;
        if (cudaOccupancyMaxActiveClusters(&clusters, dwsep_kernel, &cfg) != cudaSuccess || clusters < 1) {
            (void)cudaGetLastError();
            clusters = sms / 2;
        }
        grid = 2 * (clusters < sms / 2 ? clusters : sms / 2);
    }

    CUtensorMap tm_w, tm_x0, tm_x, tm_o, tm_s;
    auto make_map = [&](CUtensorMap* m, const void* base, int rank, const cuuint64_t* dims, const cuuint64_t* strides,
                        const cuuint32_t* box, CUtensorMapL2promotion promo,
                        CUtensorMapSwizzle swizzle = CU_TENSOR_MAP_SWIZZLE_128B) {
        const cuuint32_t ones[4] = {1, 1, 1, 1};
        encode(m, CU_TENSOR_MAP_DATA_TYPE_BFLOAT16, rank, (void*)base, dims, strides, box, ones,
               CU_TENSOR_MAP_INTERLEAVE_NONE, swizzle, promo, CU_TENSOR_MAP_FLOAT_OOB_FILL_NONE);
    };
    {
        const cuuint64_t dims[3] = {64, kC, 6}, strides[2] = {kC * 2, 128};
        const cuuint32_t box[3] = {64, 64, 3};
        make_map(&tm_w, pw, 3, dims, strides, box, CU_TENSOR_MAP_L2_PROMOTION_L2_128B);
    }
    {
        const cuuint64_t dims[4] = {64, 8, 6, (cuuint64_t)pixels / 8}, strides[3] = {kC * 2, 128, kC * 2 * 8};
        const cuuint32_t box0[4] = {64, 8, 2, 8}, box[4] = {64, 8, 6, kTilePx / 8};
        make_map(&tm_x0, x, 4, dims, strides, box0, CU_TENSOR_MAP_L2_PROMOTION_L2_128B);
        make_map(&tm_x, x, 4, dims, strides, box, CU_TENSOR_MAP_L2_PROMOTION_L2_128B);
    }
    {
        const cuuint64_t dims[2] = {8, (cuuint64_t)pixels * 6}, strides[1] = {128};
        const cuuint32_t box[2] = {8, kStageBytes / 128};
        make_map(&tm_s, x, 2, dims, strides, box, CU_TENSOR_MAP_L2_PROMOTION_L2_128B, CU_TENSOR_MAP_SWIZZLE_NONE);
    }
    {
        const cuuint64_t dims[3] = {64, 6, (cuuint64_t)pixels}, strides[2] = {128, kC * 2};
        const cuuint32_t box[3] = {64, 3, kTilePx};
        make_map(&tm_o, d_out, 3, dims, strides, box, CU_TENSOR_MAP_L2_PROMOTION_NONE);
    }
    dwsep_kernel<<<grid, kThreads, kSmemBytes, cudaStreamPerThread>>>(Inputs{{(const char*)x, (const char*)dw, (const char*)pw}}, globals, pixels / kTilePx, tm_w, tm_x0,
                                                                      tm_x, tm_o, tm_s KNOB_ARG);
}
```
